```python
import torch

def _softmax(x, axis=-1):
    return torch.softmax(x, dim=axis)
def _gelu(x):
    return torch.nn.functional.gelu(x, approximate="tanh")
def _silu(x):
    return torch.nn.functional.silu(x)
def _sigmoid(x):
    return torch.sigmoid(x)
def _layernorm(x, axis=-1, eps=1e-5):
    m = x.mean(dim=axis, keepdim=True)
    v = x.var(dim=axis, keepdim=True, unbiased=False)
    return (x - m) / torch.sqrt(v + eps)
def _scatter_add(tgt, idx, src, axis=0):
    return tgt.clone().index_add_(axis, idx, src)
def _segment_sum(src, seg, n):
    out = torch.zeros((n,) + src.shape[1:], dtype=src.dtype)
    return out.index_add_(0, seg, src)
def _pad(x, pw):
    flat = tuple(v for pair in reversed(pw) for v in pair)
    return torch.nn.functional.pad(x, flat)

kernel_name = 'gather_scatter__cheap_equivariant_egnn__graph'

def setup_inputs():

    _w = (lambda a: (lambda t: t.to(torch.bfloat16) if t.is_floating_point() else t)(torch.as_tensor(a)))
    N, deg, D, De = 25000, 32, 64, max(16, 1)
    E = N * deg
    return {
        "h": _w((lambda *s: torch.randn(*s, dtype=torch.bfloat16) * 0.2)(N, D)),
        "pos": _w((lambda *s: torch.randn(*s, dtype=torch.bfloat16) * 0.8)(N, 3)),
        "e_attr": _w((lambda *s: torch.randn(*s, dtype=torch.bfloat16) * 0.8)(E, De)),
        "src": _w((lambda lo, hi, *s: torch.randint(lo, hi, s))(0, N, E).to(torch.int64)),
        "dst": _w((lambda lo, hi, *s: torch.randint(lo, hi, s))(0, N, E).to(torch.int64)),
        "w_e": _w(0.1 * (lambda *s: torch.randn(*s, dtype=torch.bfloat16) * 0.8)(2 * D + 1 + De, D)),
        "w_x": _w(0.1 * (lambda *s: torch.randn(*s, dtype=torch.bfloat16) * 0.2)(D, 1)),
        "w_h": _w(0.1 * (lambda *s: torch.randn(*s, dtype=torch.bfloat16) * 0.2)(2 * D, D)),
    }

def reference(h, pos, e_attr, src, dst, w_e, w_x, w_h):
    N, D = h.shape[0], h.shape[1]
    diff = pos[dst] - pos[src]
    dist2 = torch.sum(diff * diff, axis=-1, keepdims=True)
    e_in = torch.concatenate([h[dst], h[src], dist2, e_attr], axis=-1)
    m_ij = _silu(e_in @ w_e)
    coord_scale = m_ij @ w_x
    pos_new = pos + _segment_sum(diff * coord_scale, dst, N)
    m_i = _segment_sum(m_ij, dst, N)
    h_new = h + _silu(torch.concatenate([h, m_i], axis=-1) @ w_h)
    return h_new, pos_new
```

```cpp
#include <cuda_runtime.h>
#include <cuda_bf16.h>
#include <stdint.h>

typedef unsigned int u32;
typedef unsigned long long u64;
#define DEVI __device__ __forceinline__

constexpr int NN = 25000, NE = 800000;
constexpr int NCTA = 132, NT = 512, NPC = 190, CHUNK = 6064, CAP = 6656, MAXPOS = 7136;
constexpr int RPT = 13;
constexpr int S_POS = 0, S_REC = 150016, S_W1 = 198528, S_W2 = S_W1 + 8192, S_WH = S_W1 + 16384;
constexpr int S_CNT = S_WH + 16384, S_DEL = S_CNT + 528, S_MB = S_DEL + 528, S_VAR = S_MB + 8, S_END = S_VAR + 24;
constexpr int S_SO = 0, S_ED = MAXPOS * 4, S_G = MAXPOS * 8, S_STG = MAXPOS * 16, STG = 2560;
constexpr int S_LP = S_STG + 32 * STG, S_GC = S_LP + 1536;
static_assert(S_GC + 128 <= S_W1 && S_END <= 232448, "smem");

__device__ uint2 g_list[NCTA * CAP];
__device__ uint4 g_B[NN * 8];
__device__ u32 g_cnt[NCTA * 8];
__device__ u32 g_bar, g_novf;
__device__ u32 g_ovf[NE];
__device__ float g_acc[NN * 68];

DEVI u32 lds32(u32 a) { u32 v; asm volatile("ld.shared.u32 %0,[%1];" : "=r"(v) : "r"(a)); return v; }
DEVI uint2 lds64(u32 a) { uint2 v; asm volatile("ld.shared.v2.u32 {%0,%1},[%2];" : "=r"(v.x), "=r"(v.y) : "r"(a)); return v; }
DEVI uint4 lds128(u32 a) { uint4 v; asm volatile("ld.shared.v4.u32 {%0,%1,%2,%3},[%4];" : "=r"(v.x), "=r"(v.y), "=r"(v.z), "=r"(v.w) : "r"(a)); return v; }
DEVI void sts32(u32 a, u32 v) { asm volatile("st.shared.u32 [%0],%1;" ::"r"(a), "r"(v) : "memory"); }
DEVI void sts64(u32 a, u32 x, u32 y) { asm volatile("st.shared.v2.u32 [%0],{%1,%2};" ::"r"(a), "r"(x), "r"(y) : "memory"); }
DEVI void sts128(u32 a, uint4 v) { asm volatile("st.shared.v4.u32 [%0],{%1,%2,%3,%4};" ::"r"(a), "r"(v.x), "r"(v.y), "r"(v.z), "r"(v.w) : "memory"); }
DEVI u32 atoms_inc(u32 a) { u32 v; asm volatile("atom.shared.add.u32 %0,[%1],1;" : "=r"(v) : "r"(a) : "memory"); return v; }
DEVI void ldsm4(u32 a, u32* r) { asm volatile("ldmatrix.sync.aligned.m8n8.x4.shared.b16 {%0,%1,%2,%3},[%4];" : "=r"(r[0]), "=r"(r[1]), "=r"(r[2]), "=r"(r[3]) : "r"(a)); }
DEVI void ldsm4t(u32 a, u32* r) { asm volatile("ldmatrix.sync.aligned.m8n8.x4.trans.shared.b16 {%0,%1,%2,%3},[%4];" : "=r"(r[0]), "=r"(r[1]), "=r"(r[2]), "=r"(r[3]) : "r"(a)); }
DEVI u32 ldsm1t(u32 a) { u32 r; asm volatile("ldmatrix.sync.aligned.m8n8.x1.trans.shared.b16 {%0},[%1];" : "=r"(r) : "r"(a)); return r; }
DEVI u32 movm(u32 a) { u32 r; asm("movmatrix.sync.aligned.m8n8.trans.b16 %0,%1;" : "=r"(r) : "r"(a)); return r; }
DEVI void mma16(float* c, u32 a0, u32 a1, u32 a2, u32 a3, u32 b0, u32 b1) {
  asm("mma.sync.aligned.m16n8k16.row.col.f32.bf16.bf16.f32 {%0,%1,%2,%3},{%4,%5,%6,%7},{%8,%9},{%0,%1,%2,%3};"
      : "+f"(c[0]), "+f"(c[1]), "+f"(c[2]), "+f"(c[3]) : "r"(a0), "r"(a1), "r"(a2), "r"(a3), "r"(b0), "r"(b1));
}
DEVI void mma8(float* c, u32 a0, u32 a1, u32 b0) {
  asm("mma.sync.aligned.m16n8k8.row.col.f32.bf16.bf16.f32 {%0,%1,%2,%3},{%4,%5},{%6},{%0,%1,%2,%3};"
      : "+f"(c[0]), "+f"(c[1]), "+f"(c[2]), "+f"(c[3]) : "r"(a0), "r"(a1), "r"(b0));
}
DEVI u32 pack2(float lo, float hi) { u32 r; asm("cvt.rn.bf16x2.f32 %0,%1,%2;" : "=r"(r) : "f"(hi), "f"(lo)); return r; }
DEVI u32 hmul2(u32 a, u32 b) { u32 r; asm("mul.rn.bf16x2 %0,%1,%2;" : "=r"(r) : "r"(a), "r"(b)); return r; }
DEVI u32 hadd2(u32 a, u32 b) { u32 r; asm("add.rn.bf16x2 %0,%1,%2;" : "=r"(r) : "r"(a), "r"(b)); return r; }
DEVI u32 hsub2(u32 a, u32 b) { u32 r; asm("sub.rn.bf16x2 %0,%1,%2;" : "=r"(r) : "r"(a), "r"(b)); return r; }
DEVI u32 hfma2(u32 a, u32 b, u32 c) { u32 r; asm("fma.rn.bf16x2 %0,%1,%2,%3;" : "=r"(r) : "r"(a), "r"(b), "r"(c)); return r; }
DEVI float blo(u32 v) { return __uint_as_float(v << 16); }
DEVI float bhi(u32 v) { return __uint_as_float(v & 0xffff0000u); }
DEVI float silu_h(float hx) { float t; asm("tanh.approx.f32 %0,%1;" : "=f"(t) : "f"(hx)); return fmaf(hx, t, hx); }
DEVI void cp16(u32 s, const void* g) { asm volatile("cp.async.cg.shared.global [%0],[%1],16;" ::"r"(s), "l"(g) : "memory"); }
DEVI u32 ld_acq(const u32* p) { u32 v; asm volatile("ld.acquire.gpu.global.u32 %0,[%1];" : "=r"(v) : "l"(p) : "memory"); return v; }
DEVI float b2f(__nv_bfloat16 x) { return __bfloat162float(x); }
DEVI float rbf(float x) { return __bfloat162float(__float2bfloat16_rn(x)); }

DEVI u32 bar_arrive() {
  __threadfence();
  u32 t = atomicAdd(&g_bar, 1u);
  return (t / NCTA + 1) * NCTA;
}
DEVI void bar_wait(u32 target) {
  u32 it = 0;
  while ((int)(ld_acq(&g_bar) - target) < 0) { if (++it > (1u << 26)) __trap(); }
}
DEVI void grid_sync() {
  __syncthreads();
  if (threadIdx.x == 0) bar_wait(bar_arrive());
  __syncthreads();
}

struct P {
  const __nv_bfloat16 *h, *pos, *ea; const int *src, *dst; const __nv_bfloat16 *we, *wx, *wh; __nv_bfloat16* out;
};

__device__ __noinline__ void slow_edge(const P& p, int e, int lane) {
  int s = p.src[e], d = p.dst[e];
  float df[3], d2 = 0.f;
  for (int c = 0; c < 3; c++) { df[c] = rbf(b2f(p.pos[d * 3 + c]) - b2f(p.pos[s * 3 + c])); d2 += rbf(df[c] * df[c]); }
  d2 = rbf(d2);
  const u32* w = (const u32*)p.we + lane;
  float x0 = d2 * blo(w[128 * 32]), x1 = d2 * bhi(w[128 * 32]);
  for (int k = 0; k < 64; k++) {
    float a = b2f(p.h[d * 64 + k]), b = b2f(p.h[s * 64 + k]);
    u32 wa = w[k * 32], wb = w[(64 + k) * 32];
    x0 += a * blo(wa) + b * blo(wb); x1 += a * bhi(wa) + b * bhi(wb);
  }
  for (int k = 0; k < 16; k++) { float a = b2f(p.ea[(size_t)e * 16 + k]); u32 wa = w[(129 + k) * 32]; x0 += a * blo(wa); x1 += a * bhi(wa); }
  float m0 = rbf(silu_h(0.5f * x0)), m1 = rbf(silu_h(0.5f * x1));
  float cs = m0 * b2f(p.wx[2 * lane]) + m1 * b2f(p.wx[2 * lane + 1]);
  for (int o = 16; o; o >>= 1) cs += __shfl_xor_sync(~0u, cs, o);
  cs = rbf(cs);
  atomicAdd(&g_acc[d * 68 + 2 * lane], m0); atomicAdd(&g_acc[d * 68 + 2 * lane + 1], m1);
  if (lane < 3) atomicAdd(&g_acc[d * 68 + 64 + lane], rbf((lane == 0 ? df[0] : lane == 1 ? df[1] : df[2]) * cs));
}

__device__ __noinline__ void overflow_path(const P& p, u32 novf) {
  for (int i = blockIdx.x * NT + threadIdx.x; i < NN * 68; i += NCTA * NT) g_acc[i] = 0.f;
  grid_sync();
  if (blockIdx.x == 0 && threadIdx.x == 0) g_novf = 0;
  for (u32 i = blockIdx.x * 16 + (threadIdx.x >> 5); i < novf; i += NCTA * 16) slow_edge(p, __ldcg(&g_ovf[i]), threadIdx.x & 31);
  grid_sync();
}

DEVI void gemm_perm(float (*acc)[4], const uint4* h0, const uint4* h1, u32 wbase, int lane) {
  const int r = lane & 7, b = (lane >> 3) & 1, jo = lane >> 4;
  const u32* a = (const u32*)h0; const u32* c = (const u32*)h1;
#pragma unroll
  for (int s = 0; s < 4; s++) {
    u32 row = wbase + (16 * (r >> 1) + 4 * s + (r & 1) + 2 * b) * 128;
#pragma unroll
    for (int j = 0; j < 8; j += 2) {
      u32 w[4]; ldsm4t(row + (((j + jo) ^ r) << 4), w);
      mma16(acc[j], a[2 * s], c[2 * s], a[2 * s + 1], c[2 * s + 1], w[0], w[1]);
      mma16(acc[j + 1], a[2 * s], c[2 * s], a[2 * s + 1], c[2 * s + 1], w[2], w[3]);
    }
  }
}
DEVI void load_h(const P& p, int n0, int n1, int t, uint4* h0, uint4* h1) {
  const uint4 z = make_uint4(0, 0, 0, 0);
  const uint4* hp = (const uint4*)p.h;
  h0[0] = n0 >= 0 ? __ldg(hp + n0 * 8 + 2 * t) : z; h0[1] = n0 >= 0 ? __ldg(hp + n0 * 8 + 2 * t + 1) : z;
  h1[0] = n1 >= 0 ? __ldg(hp + n1 * 8 + 2 * t) : z; h1[1] = n1 >= 0 ? __ldg(hp + n1 * 8 + 2 * t + 1) : z;
}
DEVI void st_perm(u32 base, int k, int c, int sw, uint4 v) {
  u32 a = base + k * 128 + (c >> 1) * 4; int j = 4 * (c & 1);
  sts32(a + (((j) ^ sw) << 4), v.x); sts32(a + (((j + 1) ^ sw) << 4), v.y);
  sts32(a + (((j + 2) ^ sw) << 4), v.z); sts32(a + (((j + 3) ^ sw) << 4), v.w);
}

#define TM(i)

__global__ void __launch_bounds__(NT, 1) egnn_kernel(const __grid_constant__ P p) {
  extern __shared__ __align__(128) unsigned char smem[];
  const u32 sb = (u32)__cvta_generic_to_shared(smem);
  const int tid = threadIdx.x, lane = tid & 31, warp = tid >> 5, cta = blockIdx.x;
  const int g = lane >> 2, t = lane & 3;
  TM(0);
  const int e0 = cta * CHUNK, ne4 = (min(NE, e0 + CHUNK) - e0) >> 2;
  int4 dv[3], sv[3];
#pragma unroll
  for (int k = 0; k < 3; k++) {
    int i = tid + k * NT;
    dv[k] = i < ne4 ? __ldcs((const int4*)(p.dst + e0) + i) : make_int4(-1, -1, -1, -1);
  }
#pragma unroll
  for (int k = 0; k < 3; k++) {
    int i = tid + k * NT;
    sv[k] = i < ne4 ? __ldcs((const int4*)(p.src + e0) + i) : make_int4(0, 0, 0, 0);
  }
  if (tid < NCTA) sts32(sb + S_CNT + tid * 4, 0);
  if (tid == 0) {
    asm volatile("mbarrier.init.shared.b64 [%0],1;" ::"r"(sb + S_MB) : "memory");
    asm volatile("fence.mbarrier_init.release.cluster;" ::: "memory");
    asm volatile("mbarrier.arrive.expect_tx.shared.b64 _,[%0],%1;" ::"r"(sb + S_MB), "r"(NN * 6) : "memory");
#pragma unroll
    for (int k = 0; k < 5; k++) {
      int kk = (k + cta) % 5;
      asm volatile("cp.async.bulk.shared::cluster.global.mbarrier::complete_tx::bytes [%0],[%1],%2,[%3];"
                   ::"r"(sb + S_POS + kk * 30000), "l"((const char*)p.pos + kk * 30000), "r"(30000), "r"(sb + S_MB) : "memory");
    }
  }
  int n0, n1;
  {
    int l0 = warp * 12 + g - (g >> 2), l1 = l0 + 6;
    n0 = cta * NPC + l0; n1 = n0 + 6;
    if ((g & 3) == 3 || n0 >= NN) n0 = -1;
    if ((g & 3) == 3 || l1 >= NPC || n1 >= NN) n1 = -1;
  }
  uint4 h0[2], h1[2];
  load_h(p, n0, n1, t, h0, h1);
  {
    int k = tid >> 3, c = tid & 7, sw = (k >> 4) * 2 + (k & 1);
    uint4 w1 = __ldg((const uint4*)p.we + tid), w2 = __ldg((const uint4*)p.we + 512 + tid);
    uint4 w3 = __ldg((const uint4*)p.wh + tid), w4 = __ldg((const uint4*)p.wh + 512 + tid);
    sts128(sb + S_W1 + k * 128 + ((c ^ sw) << 4), w1);
    st_perm(sb + S_W2, k, c, sw, w2);
    st_perm(sb + S_WH, k, c, sw, w3);
    st_perm(sb + S_WH + 8192, k, c, k & 7, w4);
  }
  __syncthreads();
  TM(1);
  u32 rec[12], rk[12];
#pragma unroll
  for (int k = 0; k < 12; k++) {
    int d = ((const int*)dv)[k];
    u32 o = (u32)d / NPC;
    rec[k] = ((const int*)sv)[k] | ((d - o * NPC) << 16) | (o << 24);
    if (d >= 0) rk[k] = atoms_inc(sb + S_CNT + o * 4);
  }
  __syncthreads();
  TM(2);
  u32 gb = 0, myoff = 0;
  if (tid < 160) {
    u32 c = tid < NCTA ? lds32(sb + S_CNT + tid * 4) : 0;
    if (tid < NCTA) gb = atomicAdd(&g_cnt[tid * 8], c + (1u << 24));
    u32 pre = 0;
#pragma unroll
    for (int k = 0; k < 4; k++) if (k < warp) pre += lds32(sb + S_CNT + (k * 32 + lane) * 4);
    pre = __reduce_add_sync(~0u, pre);
    u32 x = c;
#pragma unroll
    for (int o = 1; o < 32; o <<= 1) { u32 y = __shfl_up_sync(~0u, x, o); if (lane >= o) x += y; }
    myoff = pre + x - c;
    if (tid < NCTA) sts32(sb + S_DEL + tid * 4, myoff);
  }
  {
    float acc[8][4];
#pragma unroll
    for (int j = 0; j < 8; j++) acc[j][0] = acc[j][1] = acc[j][2] = acc[j][3] = 0.f;
    gemm_perm(acc, h0, h1, sb + S_W2, lane);
    u32 o0[8], o1[8];
#pragma unroll
    for (int j = 0; j < 8; j++) { o0[j] = pack2(0.5f * acc[j][0], 0.5f * acc[j][1]); o1[j] = pack2(0.5f * acc[j][2], 0.5f * acc[j][3]); }
    if (n0 >= 0) { g_B[n0 * 8 + 2 * t] = make_uint4(o0[0], o0[1], o0[2], o0[3]); g_B[n0 * 8 + 2 * t + 1] = make_uint4(o0[4], o0[5], o0[6], o0[7]); }
    if (n1 >= 0) { g_B[n1 * 8 + 2 * t] = make_uint4(o1[0], o1[1], o1[2], o1[3]); g_B[n1 * 8 + 2 * t + 1] = make_uint4(o1[4], o1[5], o1[6], o1[7]); }
  }
  __syncthreads();
  TM(3);
#pragma unroll
  for (int k = 0; k < 12; k++) {
    if (((const int*)dv)[k] >= 0) {
      u32 q = lds32(sb + S_DEL + (rec[k] >> 24) * 4) + rk[k];
      sts64(sb + S_REC + q * 8, rec[k], e0 + (tid + (k >> 2) * NT) * 4 + (k & 3));
    }
  }
  if (tid < NCTA) sts32(sb + S_CNT + tid * 4, (gb & 0xffffffu) - myoff);
  __syncthreads();
  TM(4);
#pragma unroll
  for (int k = 0; k < 12; k++) {
    int i = tid + k * NT;
    if (i < ne4 * 4) {
      uint2 r = lds64(sb + S_REC + i * 8);
      u32 o = r.x >> 24, q = i + lds32(sb + S_CNT + o * 4);
      if (q < CAP) __stcg(&g_list[o * CAP + q], r);
      else g_ovf[atomicAdd(&g_novf, 1u)] = r.y;
    }
  }
  __syncthreads();
  TM(5);
  u32 target = 0;
  if (tid == 0) target = bar_arrive();
  u32 Ac[8], X[8], W4[16], wx[8];
  {
    float acc[8][4];
#pragma unroll
    for (int j = 0; j < 8; j++) acc[j][0] = acc[j][1] = acc[j][2] = acc[j][3] = 0.f;
    const u32* we32 = (const u32*)p.we;
    u32 wd[8];
#pragma unroll
    for (int j = 0; j < 8; j++) wd[j] = __ldg(we32 + 128 * 32 + 4 * j + t);
#pragma unroll
    for (int j = 0; j < 16; j++) W4[j] = __ldg(we32 + (129 + g + 8 * ((j >> 1) & 1)) * 32 + 4 * (2 * (j >> 2) + (j & 1)) + t);
#pragma unroll
    for (int j = 0; j < 8; j++) { u32 v = __ldg((const unsigned short*)p.wx + 8 * j + g); wx[j] = v | (v << 16); }
    gemm_perm(acc, h0, h1, sb + S_W1, lane);
#pragma unroll
    for (int j = 0; j < 8; j++) {
      u32 w = hmul2(wd[j], 0x3f003f00u);
      Ac[j] = movm((g & 3) == 3 ? w : pack2(acc[j][0], acc[j][1]));
      X[j] = movm((g & 3) == 3 ? w : pack2(acc[j][2], acc[j][3]));
    }
#pragma unroll
    for (int j = 0; j < 16; j++) W4[j] = movm(hmul2(W4[j], 0x3f003f00u));
  }
  {
    u32 done, it = 0;
    do {
      asm volatile("{.reg .pred q; mbarrier.try_wait.parity.shared.b64 q,[%1],0; selp.u32 %0,1,0,q;}" : "=r"(done) : "r"(sb + S_MB) : "memory");
      if (++it > (1u << 24)) __trap();
    } while (!done);
  }
  if (tid >= 64 && tid < 64 + 192) {
    int l = tid - 64, n = min(cta * NPC + l, NN - 1);
    u32 a = sb + S_POS + ((n * 6) & ~3), x = lds32(a), y = lds32(a + 4);
    if (n & 1) { x = __funnelshift_r(x, y, 16); y >>= 16; }
    sts64(sb + S_LP + l * 8, x, y);
  } else if (warp == 8) {
    sts32(sb + S_GC + lane * 4, 0);
  } else if (tid == 32) {
    u32 v, it = 0;
    while (((v = ld_acq(&g_cnt[cta * 8])) >> 24) != NCTA) { if (++it > (1u << 26)) __trap(); }
    g_cnt[cta * 8] = 0;
    sts32(sb + S_VAR, min(v & 0xffffffu, (u32)CAP));
  } else if (tid == 0) {
    bar_wait(target);
  }
  TM(6);
  __syncthreads();
  TM(7);
  const u32 novf = __ldcg(&g_novf);
  const int cnt = lds32(sb + S_VAR);
  uint2 r[RPT]; u32 gx[RPT], gy[RPT];
#pragma unroll
  for (int k = 0; k < RPT; k++) if (tid + k * NT < cnt) r[k] = __ldcg(&g_list[cta * CAP + tid + k * NT]);
#pragma unroll
  for (int k = 0; k < RPT; k++) {
    if (tid + k * NT < cnt) {
      u32 s = r[k].x & 0xffff, dl = (r[k].x >> 16) & 0xff;
      u32 a = sb + S_POS + ((s * 6) & ~3), x = lds32(a), y = lds32(a + 4);
      uint2 pd = lds64(sb + S_LP + dl * 8);
      u32 grp = (dl * 171) >> 10, sl = dl - grp * 6;
      u32 rank = atoms_inc(sb + S_GC + grp * 4);
      u32 sh = (s & 1) << 4;
      x = __funnelshift_r(x, y, sh); y >>= sh;
      x = hsub2(pd.x, x); y = hsub2(pd.y, y);
      u32 qx = hmul2(x, x), qy = hmul2(y, y);
      gx[k] = x; gy[k] = pack2(blo(y), blo(qx) + bhi(qx) + blo(qy));
      sl += sl >= 3;
      r[k].y = (r[k].y << 4) | (sl << 28) | (3u << 24);
      r[k].x = s | (rank << 15) | 0;
      r[k].x |= 0; gy[k] = gy[k];
      r[k].y |= grp & 15; r[k].x |= (grp >> 4) << 31;
    }
  }
  __syncthreads();
  TM(8);
  int T0, T1, T2;
  {
    u32 c = lds32(sb + S_GC + lane * 4), cp = (c + 15) & ~15u, x = cp;
#pragma unroll
    for (int o = 1; o < 32; o <<= 1) { u32 y = __shfl_up_sync(~0u, x, o); if (lane >= o) x += y; }
    u32 st = x - cp;
#pragma unroll
    for (int k = 0; k < RPT; k++) {
      u32 grp = (r[k].y & 15) | ((r[k].x >> 31) << 4);
      u32 q = __shfl_sync(~0u, st, grp) + ((r[k].x >> 15) & 0x1fff);
      if (tid + k * NT < cnt) {
        sts32(sb + S_SO + q * 4, (r[k].x & 0x7fff) << 7);
        sts32(sb + S_ED + q * 4, r[k].y);
        sts64(sb + S_G + q * 8, gx[k], gy[k]);
      }
    }
    int gsel = 2 * warp + (lane >> 4);
    u32 q = __shfl_sync(~0u, st + c, gsel) + (lane & 15), qe = __shfl_sync(~0u, x, gsel);
    if (q < qe) { sts32(sb + S_SO + q * 4, 0); sts32(sb + S_ED + q * 4, 0x33000000u); sts64(sb + S_G + q * 8, 0, 0); }
    T0 = __shfl_sync(~0u, st, 2 * warp) >> 4; T1 = __shfl_sync(~0u, x, 2 * warp) >> 4; T2 = __shfl_sync(~0u, x, 2 * warp + 1) >> 4;
  }
  if (novf) overflow_path(p, novf);
  __syncthreads();
  TM(9);
  const u32 stg = sb + S_STG + warp * 2 * STG;
  const int q4 = lane >> 3, c8 = lane & 7;
  const char* bptr = (const char*)g_B + c8 * 16;
  const char* eptr = (const char*)p.ea + (lane & 1) * 16;
  const u32 cpB = stg + (2 * q4) * 144 + c8 * 16;
  const int pr = ((lane >> 1) & 1) * 8 + (lane >> 2);
  const u32 cpE = stg + ((lane & 1) ? 2304 + pr * 16 : pr * 144 + 128);
  const u32 ldB = stg + ((lane >> 4) * 8 + c8) * 144 + (q4 & 1) * 16;
  const u32 ldE = stg + ((q4 & 1) ? 2304 + ((lane >> 4) * 8 + c8) * 16 : ((lane >> 4) * 8 + c8) * 144 + 128);
  const u32 tlo = g < 3 ? 0x3fu << (8 * g) : 0, thi = (g >= 4 && g < 7) ? 0x3fu << (8 * (g - 4)) : 0;
  auto issue = [&](int tile, u32 off) {
    uint4 so = lds128(sb + S_SO + tile * 64 + q4 * 16);
    u32 ed = lds32(sb + S_ED + tile * 64 + (lane >> 1) * 4);
    cp16(cpB + off, bptr + so.x); cp16(cpB + off + 8 * 144, bptr + so.y);
    cp16(cpB + off + 144, bptr + so.z); cp16(cpB + off + 9 * 144, bptr + so.w);
    cp16(cpE + off, eptr + (size_t)(ed & 0xfffff0u) * 2);
  };
  u32 off = 0;
  int tile = T0, tend = T1;
  if (tile < T2) issue(tile, 0);
  asm volatile("cp.async.commit_group;" ::: "memory");
#pragma unroll 1
  for (int gi = 0; gi < 2; gi++) {
    float seg[4][4], pa[4];
#pragma unroll
    for (int j = 0; j < 4; j++) { seg[j][0] = seg[j][1] = seg[j][2] = seg[j][3] = 0.f; pa[j] = 0.f; }
#pragma unroll 1
    for (; tile < tend; tile++) {
      __syncwarp();
      if (tile + 1 < T2) issue(tile + 1, STG - off);
      asm volatile("cp.async.commit_group;" ::: "memory");
      uint4 ed = lds128(sb + S_ED + tile * 64 + t * 16);
      u32 vG = ldsm1t(sb + S_G + tile * 128 + c8 * 16);
      u32 sa = __byte_perm(tlo, thi, __byte_perm(ed.x, ed.z, 0x73)), sbb = __byte_perm(tlo, thi, __byte_perm(ed.y, ed.w, 0x73));
      sa = g == 3 ? vG : sa; sbb = g == 7 ? vG : sbb;
      u32 ta = movm(sa), tb = movm(sbb);
      asm volatile("cp.async.wait_group 1;" ::: "memory");
      __syncwarp();
      u32 ef[4]; ldsm4(ldE + off, ef);
      u32 ca = 0, cb = 0;
#pragma unroll
      for (int mt = 0; mt < 4; mt++) {
        u32 b[4]; ldsm4t(ldB + off + mt * 32, b);
        float x[4] = {blo(b[0]), bhi(b[0]), blo(b[1]), bhi(b[1])}, y[4] = {blo(b[2]), bhi(b[2]), blo(b[3]), bhi(b[3])};
        mma16(x, W4[4 * mt], W4[4 * mt + 1], W4[4 * mt + 2], W4[4 * mt + 3], ef[0], ef[1]);
        mma16(y, W4[4 * mt], W4[4 * mt + 1], W4[4 * mt + 2], W4[4 * mt + 3], ef[2], ef[3]);
        mma8(x, Ac[2 * mt], Ac[2 * mt + 1], ta);
        mma8(y, Ac[2 * mt], Ac[2 * mt + 1], tb);
        u32 m0 = pack2(silu_h(x[0]), silu_h(x[1])), m1 = pack2(silu_h(x[2]), silu_h(x[3]));
        u32 m2 = pack2(silu_h(y[0]), silu_h(y[1])), m3 = pack2(silu_h(y[2]), silu_h(y[3]));
        mma16(seg[mt], m0, m1, m2, m3, sa, sbb);
        ca = mt ? hfma2(m0, wx[2 * mt], ca) : hmul2(m0, wx[0]); cb = mt ? hfma2(m2, wx[2 * mt], cb) : hmul2(m2, wx[0]);
        ca = hfma2(m1, wx[2 * mt + 1], ca); cb = hfma2(m3, wx[2 * mt + 1], cb);
      }
      u32 keep = g < 4 ? ca : cb, send = g < 4 ? cb : ca;
      keep = hadd2(keep, __shfl_xor_sync(~0u, send, 16));
      keep = hadd2(keep, __shfl_xor_sync(~0u, keep, 8));
      keep = hadd2(keep, __shfl_xor_sync(~0u, keep, 4));
      mma8(pa, sa, sbb, hmul2(keep, vG));
      off = STG - off;
    }
    const int nd = gi ? n1 : n0;
    if (novf) {
      int na = __shfl_sync(~0u, nd, 8 * t), nb = __shfl_sync(~0u, nd, 8 * t + 4);
#pragma unroll
      for (int mt = 0; mt < 4; mt++) {
        if (na >= 0) { seg[mt][0] += 0.5f * __ldcg(&g_acc[na * 68 + 16 * mt + g]); seg[mt][2] += 0.5f * __ldcg(&g_acc[na * 68 + 16 * mt + 8 + g]); }
        if (nb >= 0) { seg[mt][1] += 0.5f * __ldcg(&g_acc[nb * 68 + 16 * mt + g]); seg[mt][3] += 0.5f * __ldcg(&g_acc[nb * 68 + 16 * mt + 8 + g]); }
      }
      if (nd >= 0 && t < 2) { pa[0] += 0.5f * __ldcg(&g_acc[nd * 68 + 64 + 2 * t]); pa[1] += 0.5f * __ldcg(&g_acc[nd * 68 + 65 + 2 * t]); }
    }
    float u0 = pa[0] + __shfl_xor_sync(~0u, pa[2], 2), u1 = pa[1] + __shfl_xor_sync(~0u, pa[3], 2);
    if (nd >= 0 && t < 2) {
      u32 pv = lds32(sb + S_LP + (nd - cta * NPC) * 8 + t * 4);
      u32 o = hadd2(pv, pack2(2.f * u0, 2.f * u1));
      unsigned short* po = (unsigned short*)p.out + NN * 64 + nd * 3 + 2 * t;
      po[0] = o & 0xffff;
      if (t == 0) po[1] = o >> 16;
    }
#pragma unroll
    for (int mt = 0; mt < 4; mt++) {
      Ac[2 * mt] = X[2 * mt]; Ac[2 * mt + 1] = X[2 * mt + 1];
      X[2 * mt] = movm(pack2(2.f * seg[mt][0], 2.f * seg[mt][1]));
      X[2 * mt + 1] = movm(pack2(2.f * seg[mt][2], 2.f * seg[mt][3]));
    }
    tend = T2;
  }
  TM(10);
  {
    load_h(p, n0, n1, t, h0, h1);
    float acc[8][4];
#pragma unroll
    for (int j = 0; j < 8; j++) acc[j][0] = acc[j][1] = acc[j][2] = acc[j][3] = 0.f;
#pragma unroll
    for (int s = 0; s < 4; s++) {
      u32 row = sb + S_WH + 8192 + (16 * s + (lane & 15)) * 128;
#pragma unroll
      for (int j = 0; j < 8; j += 2) {
        u32 w[4]; ldsm4t(row + (((j + (lane >> 4)) ^ c8) << 4), w);
        mma16(acc[j], Ac[2 * s], X[2 * s], Ac[2 * s + 1], X[2 * s + 1], w[0], w[1]);
        mma16(acc[j + 1], Ac[2 * s], X[2 * s], Ac[2 * s + 1], X[2 * s + 1], w[2], w[3]);
      }
    }
    gemm_perm(acc, h0, h1, sb + S_WH, lane);
    u32* a = (u32*)h0; u32* c = (u32*)h1;
#pragma unroll
    for (int j = 0; j < 8; j++) {
      a[j] = hadd2(a[j], pack2(silu_h(0.5f * acc[j][0]), silu_h(0.5f * acc[j][1])));
      c[j] = hadd2(c[j], pack2(silu_h(0.5f * acc[j][2]), silu_h(0.5f * acc[j][3])));
    }
    uint4* o = (uint4*)p.out;
    if (n0 >= 0) { o[n0 * 8 + 2 * t] = h0[0]; o[n0 * 8 + 2 * t + 1] = h0[1]; }
    if (n1 >= 0) { o[n1 * 8 + 2 * t] = h1[0]; o[n1 * 8 + 2 * t + 1] = h1[1]; }
  }
  TM(11);
}

__global__ void fb_zero() { for (int i = blockIdx.x * blockDim.x + threadIdx.x; i < NN * 68; i += gridDim.x * blockDim.x) g_acc[i] = 0.f; }
__global__ void fb_edge(const __grid_constant__ P p) { for (int e = blockIdx.x * 8 + (threadIdx.x >> 5); e < NE; e += gridDim.x * 8) slow_edge(p, e, threadIdx.x & 31); }
__global__ void fb_node(const P p) {
  int n = blockIdx.x, f = threadIdx.x;
  float x = 0.f;
  for (int k = 0; k < 64; k++) x += b2f(p.h[n * 64 + k]) * b2f(p.wh[k * 64 + f]) + rbf(g_acc[n * 68 + k]) * b2f(p.wh[(64 + k) * 64 + f]);
  p.out[n * 64 + f] = __float2bfloat16_rn(b2f(p.h[n * 64 + f]) + rbf(silu_h(0.5f * x)));
  if (f < 3) p.out[NN * 64 + n * 3 + f] = __float2bfloat16_rn(b2f(p.pos[n * 3 + f]) + rbf(g_acc[n * 68 + 64 + f]));
}

extern "C" void kernel_launch(void* const* d_in, const int* in_sizes, int n_in, void* d_out, int out_size) {
  static int mode = -1;
  if (mode < 0) {
    int dev = 0, sms = 0, occ = 0;
    cudaGetDevice(&dev);
    cudaDeviceGetAttribute(&sms, cudaDevAttrMultiProcessorCount, dev);
    cudaError_t e = cudaFuncSetAttribute(egnn_kernel, cudaFuncAttributeMaxDynamicSharedMemorySize, S_END);
    if (e == cudaSuccess) e = cudaOccupancyMaxActiveBlocksPerMultiprocessor(&occ, egnn_kernel, NT, S_END);
    mode = (e == cudaSuccess && occ * sms >= NCTA) ? 1 : 0;
    cudaGetLastError();
  }
  P p;
  p.h = (const __nv_bfloat16*)d_in[0]; p.pos = (const __nv_bfloat16*)d_in[1]; p.ea = (const __nv_bfloat16*)d_in[2];
  p.src = (const int*)d_in[3]; p.dst = (const int*)d_in[4];
  p.we = (const __nv_bfloat16*)d_in[5]; p.wx = (const __nv_bfloat16*)d_in[6]; p.wh = (const __nv_bfloat16*)d_in[7];
  p.out = (__nv_bfloat16*)d_out;
  if (mode == 1) {
    egnn_kernel<<<NCTA, NT, S_END>>>(p);
  } else {
    fb_zero<<<512, 256>>>(); fb_edge<<<2048, 256>>>(p); fb_node<<<NN, 64>>>(p);
  }
}
```

```cpp
#include <cuda_runtime.h>
#include <cuda_bf16.h>
#include <stdint.h>

#pragma nv_diag_suppress 549
typedef unsigned int u32;
typedef unsigned long long u64;
#define DEVI __device__ __forceinline__

constexpr int NN = 25000, NE = 800000;
constexpr int NCTA = 132, NT = 512, NPC = 190, CHUNK = 6064, CAP = 6656, MAXPOS = 7136;
constexpr int RPT = 13;
constexpr int S_POS = 0, S_REC = 150016, S_A = S_REC, S_LP = S_A + 193 * 128;
constexpr int S_CNT = S_REC + (CHUNK + 3 * NCTA) * 8, S_DEL = S_CNT + 528, S_GB = S_DEL + 528, S_MB = S_GB + 528, S_GC = 199056, S_VAR = S_GC + 256;
constexpr int S_X = 199680, S_WH = S_X + 16384, S_W1 = S_WH, S_W2 = S_W1 + 8192, S_END = S_WH + 16384, S_W4 = S_X + 5120;
constexpr int S_SO = 0, S_ED = MAXPOS * 4, S_G = MAXPOS * 8, S_STG = MAXPOS * 16, STG = 2560, S_ST = S_STG + 32 * STG;
static_assert(S_LP + NPC * 128 <= S_GC && S_VAR + 8 <= S_X && S_MB + 8 <= S_W4 && S_ST + 2048 + 256 <= S_GC && S_END <= 232448, "smem");

__device__ __align__(128) uint2 g_list[NCTA * CAP];
__device__ __align__(128) uint4 g_B[NN * 8];
__device__ u32 g_cnt[NCTA * 8];
__device__ u32 g_bar, g_novf, g_bar2[64];
__device__ u32 g_ovf[NE];
__device__ float g_acc[NN * 68];

DEVI u32 lds32(u32 a) { u32 v; asm volatile("ld.shared.u32 %0,[%1];" : "=r"(v) : "r"(a)); return v; }
DEVI uint2 lds64(u32 a) { uint2 v; asm volatile("ld.shared.v2.u32 {%0,%1},[%2];" : "=r"(v.x), "=r"(v.y) : "r"(a)); return v; }
DEVI uint4 lds128(u32 a) { uint4 v; asm volatile("ld.shared.v4.u32 {%0,%1,%2,%3},[%4];" : "=r"(v.x), "=r"(v.y), "=r"(v.z), "=r"(v.w) : "r"(a)); return v; }
DEVI void sts32(u32 a, u32 v) { asm volatile("st.shared.u32 [%0],%1;" ::"r"(a), "r"(v) : "memory"); }
DEVI void sts64(u32 a, u32 x, u32 y) { asm volatile("st.shared.v2.u32 [%0],{%1,%2};" ::"r"(a), "r"(x), "r"(y) : "memory"); }
DEVI void sts128(u32 a, uint4 v) { asm volatile("st.shared.v4.u32 [%0],{%1,%2,%3,%4};" ::"r"(a), "r"(v.x), "r"(v.y), "r"(v.z), "r"(v.w) : "memory"); }
DEVI u32 atoms_inc(u32 a) { u32 v; asm volatile("atom.shared.add.u32 %0,[%1],1;" : "=r"(v) : "r"(a) : "memory"); return v; }
DEVI void ldsm4(u32 a, u32* r) { asm volatile("ldmatrix.sync.aligned.m8n8.x4.shared.b16 {%0,%1,%2,%3},[%4];" : "=r"(r[0]), "=r"(r[1]), "=r"(r[2]), "=r"(r[3]) : "r"(a)); }
DEVI void ldsm4t(u32 a, u32* r) { asm volatile("ldmatrix.sync.aligned.m8n8.x4.trans.shared.b16 {%0,%1,%2,%3},[%4];" : "=r"(r[0]), "=r"(r[1]), "=r"(r[2]), "=r"(r[3]) : "r"(a)); }
DEVI u32 ldsm1t(u32 a) { u32 r; asm volatile("ldmatrix.sync.aligned.m8n8.x1.trans.shared.b16 {%0},[%1];" : "=r"(r) : "r"(a)); return r; }
DEVI u32 movm(u32 a) { u32 r; asm("movmatrix.sync.aligned.m8n8.trans.b16 %0,%1;" : "=r"(r) : "r"(a)); return r; }
DEVI void mma16(float* c, u32 a0, u32 a1, u32 a2, u32 a3, u32 b0, u32 b1) {
  asm("mma.sync.aligned.m16n8k16.row.col.f32.bf16.bf16.f32 {%0,%1,%2,%3},{%4,%5,%6,%7},{%8,%9},{%0,%1,%2,%3};"
      : "+f"(c[0]), "+f"(c[1]), "+f"(c[2]), "+f"(c[3]) : "r"(a0), "r"(a1), "r"(a2), "r"(a3), "r"(b0), "r"(b1));
}
DEVI void mma8(float* c, u32 a0, u32 a1, u32 b0) {
  asm("mma.sync.aligned.m16n8k8.row.col.f32.bf16.bf16.f32 {%0,%1,%2,%3},{%4,%5},{%6},{%0,%1,%2,%3};"
      : "+f"(c[0]), "+f"(c[1]), "+f"(c[2]), "+f"(c[3]) : "r"(a0), "r"(a1), "r"(b0));
}
DEVI u32 pack2(float lo, float hi) { u32 r; asm("cvt.rn.bf16x2.f32 %0,%1,%2;" : "=r"(r) : "f"(hi), "f"(lo)); return r; }
DEVI u32 pack2z(float lo, float hi) { u32 r; asm("cvt.rz.bf16x2.f32 %0,%1,%2;" : "=r"(r) : "f"(hi), "f"(lo)); return r; }
DEVI u32 hfma2l(u32 a, u32 b, u32 c) { u32 r; asm("{.reg .b16 l,h; .reg .b32 d; mov.b32 {l,h},%2; mov.b32 d,{l,l}; fma.rn.bf16x2 %0,%1,d,%3;}" : "=r"(r) : "r"(a), "r"(b), "r"(c)); return r; }
DEVI u32 hfma2h(u32 a, u32 b, u32 c) { u32 r; asm("{.reg .b16 l,h; .reg .b32 d; mov.b32 {l,h},%2; mov.b32 d,{h,h}; fma.rn.bf16x2 %0,%1,d,%3;}" : "=r"(r) : "r"(a), "r"(b), "r"(c)); return r; }
DEVI int node_of(int l0, int g, int cta) { int l = l0 + g - (g >> 2), n = cta * NPC + l; return ((g & 3) == 3 || l >= NPC || n >= NN) ? -1 : n; }
DEVI u32 hmul2(u32 a, u32 b) { u32 r; asm("mul.rn.bf16x2 %0,%1,%2;" : "=r"(r) : "r"(a), "r"(b)); return r; }
DEVI u32 hadd2(u32 a, u32 b) { u32 r; asm("add.rn.bf16x2 %0,%1,%2;" : "=r"(r) : "r"(a), "r"(b)); return r; }
DEVI u32 hsub2(u32 a, u32 b) { u32 r; asm("sub.rn.bf16x2 %0,%1,%2;" : "=r"(r) : "r"(a), "r"(b)); return r; }
DEVI u32 hfma2(u32 a, u32 b, u32 c) { u32 r; asm("fma.rn.bf16x2 %0,%1,%2,%3;" : "=r"(r) : "r"(a), "r"(b), "r"(c)); return r; }
DEVI u32 prmt(u32 a, u32 b, u32 c) { u32 r; asm("prmt.b32 %0,%1,%2,%3;" : "=r"(r) : "r"(a), "r"(b), "r"(c)); return r; }
DEVI float blo(u32 v) { return __uint_as_float(v << 16); }
DEVI float bhi(u32 v) { return __uint_as_float(v & 0xffff0000u); }
#define DBG 0
DEVI float silu_h(float hx) { float t; if (DBG & 2) return fmaf(hx, hx, hx); asm("tanh.approx.f32 %0,%1;" : "=f"(t) : "f"(hx)); return fmaf(hx, t, hx); }
DEVI void cp16(u32 s, const void* g) { asm volatile("cp.async.cg.shared.global [%0],[%1],16;" ::"r"(s), "l"(g) : "memory"); }
DEVI const void* madw(u32 a, u32 b, const void* c) { const void* r; asm("mad.wide.u32 %0,%1,%2,%3;" : "=l"(r) : "r"(a), "r"(b), "l"(c)); return r; }
DEVI u32 ld_acq(const u32* p) { u32 v; asm volatile("ld.acquire.gpu.global.u32 %0,[%1];" : "=r"(v) : "l"(p) : "memory"); return v; }
DEVI float b2f(__nv_bfloat16 x) { return __bfloat162float(x); }
DEVI float rbf(float x) { return __bfloat162float(__float2bfloat16_rn(x)); }

DEVI u32 bar_arrive() {
  __threadfence();
  u32 t = atomicAdd(&g_bar, 1u);
  return (t / NCTA + 1) * NCTA;
}
DEVI void bar_wait(u32 target, const u32* bar = &g_bar) {
  u32 it = 0;
  while ((int)(ld_acq(bar) - target) < 0) { if (++it > (1u << 26)) __trap(); }
}
DEVI void grid_sync() {
  __syncthreads();
  if (threadIdx.x == 0) bar_wait(bar_arrive());
  __syncthreads();
}

struct P {
  const __nv_bfloat16 *h, *pos, *ea; const int *src, *dst; const __nv_bfloat16 *we, *wx, *wh; __nv_bfloat16* out;
};

__device__ __noinline__ void slow_edge(const P& p, int e, int lane) {
  int s = p.src[e], d = p.dst[e];
  float df[3], d2 = 0.f;
  for (int c = 0; c < 3; c++) { df[c] = rbf(b2f(p.pos[d * 3 + c]) - b2f(p.pos[s * 3 + c])); d2 += rbf(df[c] * df[c]); }
  d2 = rbf(d2);
  const u32* w = (const u32*)p.we + lane;
  float x0 = d2 * blo(w[128 * 32]), x1 = d2 * bhi(w[128 * 32]);
  for (int k = 0; k < 64; k++) {
    float a = b2f(p.h[d * 64 + k]), b = b2f(p.h[s * 64 + k]);
    u32 wa = w[k * 32], wb = w[(64 + k) * 32];
    x0 += a * blo(wa) + b * blo(wb); x1 += a * bhi(wa) + b * bhi(wb);
  }
  for (int k = 0; k < 16; k++) { float a = b2f(p.ea[(size_t)e * 16 + k]); u32 wa = w[(129 + k) * 32]; x0 += a * blo(wa); x1 += a * bhi(wa); }
  float m0 = rbf(silu_h(0.5f * x0)), m1 = rbf(silu_h(0.5f * x1));
  float cs = m0 * b2f(p.wx[2 * lane]) + m1 * b2f(p.wx[2 * lane + 1]);
  for (int o = 16; o; o >>= 1) cs += __shfl_xor_sync(~0u, cs, o);
  cs = rbf(cs);
  atomicAdd(&g_acc[d * 68 + 2 * lane], m0); atomicAdd(&g_acc[d * 68 + 2 * lane + 1], m1);
  if (lane < 3) atomicAdd(&g_acc[d * 68 + 64 + lane], rbf((lane == 0 ? df[0] : lane == 1 ? df[1] : df[2]) * cs));
}

__device__ __noinline__ void overflow_path(const P& p, u32 novf) {
  for (int i = blockIdx.x * NT + threadIdx.x; i < NN * 68; i += NCTA * NT) g_acc[i] = 0.f;
  grid_sync();
  if (blockIdx.x == 0 && threadIdx.x == 0) g_novf = 0;
  for (u32 i = blockIdx.x * 16 + (threadIdx.x >> 5); i < novf; i += NCTA * 16) slow_edge(p, __ldcg(&g_ovf[i]), threadIdx.x & 31);
  grid_sync();
}

DEVI void gemm_perm(float (*acc)[4], const uint4* h0, const uint4* h1, u32 wbase, int lane) {
  const int r = lane & 7, b = (lane >> 3) & 1, jo = lane >> 4;
  const u32* a = (const u32*)h0; const u32* c = (const u32*)h1;
#pragma unroll
  for (int s = 0; s < 4; s++) {
    u32 row = wbase + (16 * (r >> 1) + 4 * s + (r & 1) + 2 * b) * 128;
#pragma unroll
    for (int j = 0; j < 8; j += 2) {
      u32 w[4]; ldsm4t(row + (((j + jo) ^ r) << 4), w);
      mma16(acc[j], a[2 * s], c[2 * s], a[2 * s + 1], c[2 * s + 1], w[0], w[1]);
      mma16(acc[j + 1], a[2 * s], c[2 * s], a[2 * s + 1], c[2 * s + 1], w[2], w[3]);
    }
  }
}
DEVI void load_h(const P& p, int n0, int n1, int t, uint4* h0, uint4* h1) {
  const uint4 z = make_uint4(0, 0, 0, 0);
  const uint4* hp = (const uint4*)p.h;
  h0[0] = n0 >= 0 ? __ldg(hp + n0 * 8 + 2 * t) : z; h0[1] = n0 >= 0 ? __ldg(hp + n0 * 8 + 2 * t + 1) : z;
  h1[0] = n1 >= 0 ? __ldg(hp + n1 * 8 + 2 * t) : z; h1[1] = n1 >= 0 ? __ldg(hp + n1 * 8 + 2 * t + 1) : z;
}
DEVI void st_perm(u32 base, int k, int c, int sw, uint4 v) {
  u32 a = base + k * 128 + (c >> 1) * 4; int j = 4 * (c & 1);
  sts32(a + (((j) ^ sw) << 4), v.x); sts32(a + (((j + 1) ^ sw) << 4), v.y);
  sts32(a + (((j + 2) ^ sw) << 4), v.z); sts32(a + (((j + 3) ^ sw) << 4), v.w);
}

#define P1 5
#define P2 5
#define NG 4
#define UNR 1
#define PF 0
constexpr int UNRC = UNR;
#define TM(i)

__global__ void __launch_bounds__(NT, 1) egnn_kernel(const __grid_constant__ P p) {
  extern __shared__ __align__(128) unsigned char smem[];
  const u32 sb = (u32)__cvta_generic_to_shared(smem);
  const int tid = threadIdx.x, lane = tid & 31, warp = tid >> 5, cta = blockIdx.x;
  const int g = lane >> 2, t = lane & 3;
  TM(0);
  u32* const sm32 = (u32*)smem;
  auto pos_tma = [&](int k0, int k1) {
    if (tid == 64) {
      for (int k = k0; k < k1; k++) {
        int kk = (k + cta) % 5;
        asm volatile("cp.async.bulk.shared::cluster.global.mbarrier::complete_tx::bytes [%0],[%1],%2,[%3];"
                     ::"r"(sb + S_POS + kk * 30000), "l"((const char*)p.pos + kk * 30000), "r"(30000), "r"(sb + S_MB) : "memory");
      }
    }
  };
  if (tid == 64) {
    asm volatile("mbarrier.init.shared.b64 [%0],1;" ::"r"(sb + S_MB) : "memory");
    asm volatile("fence.mbarrier_init.release.cluster;" ::: "memory");
    asm volatile("mbarrier.arrive.expect_tx.shared.b64 _,[%0],%1;" ::"r"(sb + S_MB), "r"(NN * 6) : "memory");
  }
  pos_tma(0, P1);
  const int e0 = cta * CHUNK, ne4 = (min(NE, e0 + CHUNK) - e0) >> 2;
  const bool v3 = tid + 2 * NT < ne4;
  int4 dv[3], sv[3];
#pragma unroll
  for (int k = 0; k < 3; k++) if (k < 2 || v3) dv[k] = __ldcs((const int4*)(p.dst + e0) + tid + k * NT);
#pragma unroll
  for (int k = 0; k < 3; k++) if (k < 2 || v3) sv[k] = __ldcs((const int4*)(p.src + e0) + tid + k * NT);
  u32 target = 0;
  if (tid < NCTA) sm32[S_CNT / 4 + tid] = 0;
  if (tid >= 14 * 32 && lane == 0) target = __ldcg(warp == 15 ? &g_bar : &g_bar2[32]);
  uint4 h0[2], h1[2];
  int n0, n1;
  {
    int l0 = warp * 16 + g;
    n0 = cta * NPC + l0; n1 = n0 + 8;
    if (l0 >= NPC || n0 >= NN) n0 = -1;
    if (l0 + 8 >= NPC || n1 >= NN) n1 = -1;
  }
  if (tid >= 239) {
    asm volatile("prefetch.global.L2 [%0];" ::"l"(tid >= 384 ? (const char*)p.wh + (tid - 384) * 128 : (const char*)p.we + (tid - 239) * 128));
  }
  __syncthreads();
  TM(1);
  u32 rec[12], rk[12];
#pragma unroll
  for (int k = 0; k < 12; k++) {
    if (k < 8 || v3) {
      u32 d = ((const int*)dv)[k], o = __umulhi(d, 22605092u);
      rk[k] = atomicAdd(sm32 + S_CNT / 4 + o, 8u);
      rec[k] = (d + o * (256 - NPC)) << 16;
    }
  }
  uint4 w1 = __ldg((const uint4*)p.we + tid), w2 = __ldg((const uint4*)p.we + 512 + tid);
  load_h(p, n0, n1, t, h0, h1);
  if (warp >= 12) h0[0] = __ldg((const uint4*)p.we + 129 * 8 + (tid - 384));
  if (warp == 12 && lane < 16) h0[1] = __ldg(lane < 8 ? (const uint4*)p.we + 128 * 8 + lane : (const uint4*)p.wx + (lane - 8));
  pos_tma(P1, P2);
  __syncthreads();
  TM(2);
  u32 gb[2], of[2], cn[2] = {0, 0};
  if (warp >= 13) {
    const int j = tid - 13 * 32;
    if (j < NCTA / 2) { uint2 c = lds64(sb + S_CNT + j * 8); cn[0] = c.x; cn[1] = c.y; }
    const u32 c0 = (cn[0] + 31) & ~31u, c1 = (cn[1] + 31) & ~31u;
    if (j < NCTA / 2) { gb[0] = atomicAdd(&g_cnt[j * 16], (c0 >> 3) + (1u << 24)); gb[1] = atomicAdd(&g_cnt[j * 16 + 8], (c1 >> 3) + (1u << 24)); }
    u32 pre = 0;
#pragma unroll
    for (int k = 0; k < 2; k++) if (k < warp - 13) { uint2 v = lds64(sb + S_CNT + (k * 32 + lane) * 8); pre += ((v.x + 31) & ~31u) + ((v.y + 31) & ~31u); }
    pre = __reduce_add_sync(~0u, pre);
    u32 x = c0 + c1;
#pragma unroll
    for (int o = 1; o < 32; o <<= 1) { u32 y = __shfl_up_sync(~0u, x, o); if (lane >= o) x += y; }
    of[1] = pre + x - c1; of[0] = of[1] - c0;
    if (j < NCTA / 2) sts64(sb + S_DEL + j * 8, of[0], of[1]);
#pragma unroll
    for (int k = 0; k < 2; k++) for (u32 i = cn[k]; i & 31; i += 8) sts64(sb + S_REC + of[k] + i, 0, ~0u);
  }
  __syncthreads();
  TM(3);
#pragma unroll
  for (int k = 0; k < 12; k++) if (k < 8 || v3) rk[k] += sm32[S_DEL / 4 + (rec[k] >> 24)];
#pragma unroll
  for (int k = 0; k < 12; k++) if (k < 8 || v3) sts64(sb + S_REC + rk[k], rec[k] | ((const int*)sv)[k], e0 + (tid + (k >> 2) * NT) * 4 + (k & 3));
  {
    int k = tid >> 3, c = tid & 7, sw = (k >> 4) * 2 + (k & 1);
    sts128(sb + S_W1 + k * 128 + ((c ^ sw) << 4), w1);
    st_perm(sb + S_W2, k, c, sw, w2);
    const u32 hf = 0x3f003f00u;
    if (warp >= 12) sts128(sb + S_W4 + (k - 48) * 128 + ((c ^ (k & 7)) << 4), make_uint4(hmul2(h0[0].x, hf), hmul2(h0[0].y, hf), hmul2(h0[0].z, hf), hmul2(h0[0].w, hf)));
    if (warp == 12 && lane < 16) sts128(sb + S_W4 + 2048 + lane * 16, h0[1]);
  }
  if (warp >= 13 && tid - 13 * 32 < NCTA / 2) sts64(sb + S_GB + (tid - 13 * 32) * 8, gb[0], gb[1]);
  asm volatile("fence.proxy.async.shared::cta;" ::: "memory");
  __syncthreads();
  TM(4);
  if (PF && warp == 13 && lane < PF) {
    int nb = min(CHUNK, NE - e0);
    asm volatile("cp.async.bulk.prefetch.L2.global [%0],%1;" ::"l"((const char*)p.ea + (size_t)e0 * 32 + lane * nb), "r"(nb) : "memory");
  }
  if (lane < (warp < 12 ? NG : (132 - 12 * NG) / 4)) {
    const u32 o = lane + (warp < 12 ? warp * NG : 12 * NG + (warp - 12) * ((132 - 12 * NG) / 4)), c = sm32[S_CNT / 4 + o], src = sb + S_REC + sm32[S_DEL / 4 + o];
    const u32 base = min((sm32[S_GB / 4 + o] & 0xffffffu) * 8, CAP * 8u), fit = min((c + 31) & ~31u, CAP * 8 - base);
    if (fit) asm volatile("cp.async.bulk.global.shared::cta.bulk_group [%0],[%1],%2; cp.async.bulk.commit_group;"
                          ::"l"((char*)g_list + o * (CAP * 8) + base), "r"(src), "r"(DBG & 16 ? 32 : fit) : "memory");
    if (fit < c) {
      u32 q = atomicAdd(&g_novf, (c - fit) >> 3);
      for (u32 i = fit; i < c; i += 8) g_ovf[q++] = lds32(src + i + 4);
    }
  }
  TM(12);
  u32 W4[16], wx[4], Ap[16];
  w1 = __ldg((const uint4*)p.wh + tid); w2 = __ldg((const uint4*)p.wh + 512 + tid);
  if (warp < 12) {
    float acc[8][4];
#pragma unroll
    for (int j = 0; j < 8; j++) acc[j][0] = acc[j][1] = acc[j][2] = acc[j][3] = 0.f;
    gemm_perm(acc, h0, h1, sb + S_W2, lane);
    asm volatile("cp.async.bulk.wait_group 0; fence.proxy.async.global; bar.arrive 1,512;" ::: "memory");
    u32 o0[8], o1[8];
#pragma unroll
    for (int j = 0; j < 8; j++) { o0[j] = pack2z(0.5f * acc[j][0], 0.5f * acc[j][1]); o1[j] = pack2z(0.5f * acc[j][2], 0.5f * acc[j][3]); }
    if (n0 >= ((DBG & 8) ? NN - 1 : 0)) { g_B[n0 * 8 + 2 * t] = make_uint4(o0[0], o0[1], o0[2], o0[3]); g_B[n0 * 8 + 2 * t + 1] = make_uint4(o0[4], o0[5], o0[6], o0[7]); }
    if (n1 >= ((DBG & 8) ? NN - 1 : 0)) { g_B[n1 * 8 + 2 * t] = make_uint4(o1[0], o1[1], o1[2], o1[3]); g_B[n1 * 8 + 2 * t + 1] = make_uint4(o1[4], o1[5], o1[6], o1[7]); }
#pragma unroll
    for (int j = 0; j < 8; j++) acc[j][0] = acc[j][1] = acc[j][2] = acc[j][3] = 0.f;
    gemm_perm(acc, h0, h1, sb + S_W1, lane);
#pragma unroll
    for (int j = 0; j < 8; j++) { Ap[2 * j] = pack2(acc[j][0], acc[j][1]); Ap[2 * j + 1] = pack2(acc[j][2], acc[j][3]); }
  } else if (warp < 15) {
    asm volatile("cp.async.bulk.wait_group 0; fence.proxy.async.global; bar.arrive 1,512;" ::: "memory");
  } else {
    asm volatile("cp.async.bulk.wait_group 0; fence.proxy.async.global; bar.sync 1,512;" ::: "memory");
    if (lane == 0) asm volatile("red.release.gpu.global.add.u32 [%0],1;" ::"l"(&g_bar) : "memory");
  }
  __syncthreads();
  TM(5);
  pos_tma(P2, 5);
  if (tid == 14 * 32) asm volatile("red.release.gpu.global.add.u32 [%0],1;" ::"l"(&g_bar2[32]) : "memory");
  if (warp < 12) {
#pragma unroll
    for (int j = 0; j < 8; j++) {
      u32 a = sb + S_A + (warp * 16 + g) * 128 + ((j ^ g) << 4) + t * 4;
      sts32(a, Ap[2 * j]); sts32(a + 1024, Ap[2 * j + 1]);
    }
  } else if (warp == 12) {
    sm32[S_GC / 4 + lane] = lane;
    sm32[(S_A + 192 * 128) / 4 + lane] = hmul2(sm32[(S_W4 + 2048) / 4 + lane], 0x3f003f00u);
  } else if (tid == 13 * 32) {
    u32 v, it = 0;
    while (((v = ld_acq(&g_cnt[cta * 8])) >> 24) != NCTA) { if (++it > (1u << 26)) __trap(); }
    g_cnt[cta * 8] = 0;
    sm32[S_VAR / 4] = min(v & 0xffffffu, (u32)CAP);
  }
  {
    u32 done, it = 0;
    do {
      asm volatile("{.reg .pred q; mbarrier.try_wait.parity.shared.b64 q,[%1],0; selp.u32 %0,1,0,q;}" : "=r"(done) : "r"(sb + S_MB) : "memory");
      if (++it > (1u << 24)) __trap();
    } while (!done);
  }
  TM(15);
#pragma unroll
  for (int k = 0; k < 2; k++) {
    int l = ((NT - 1 - tid) >> 2) + k * 128, n = min(cta * NPC + l, NN - 1);
    if (l < NPC) {
      u32 x = sm32[(n * 3) >> 1], y = sm32[((n * 3) >> 1) + 1];
      if (n & 1) { x = __funnelshift_r(x, y, 16); y >>= 16; }
      u32 grp = (l * 171) >> 10, sl = l - grp * 6;
      sl += sl >= 3;
      y = (y & 0xffff) | (grp << 18) | (sl << 28) | (3u << 24);
      u32 a = sb + S_LP + l * 128 + t * 16 + (l & 1) * 64;
      sts128(a, make_uint4(x, y, x, y)); sts128(a ^ 64, make_uint4(x, y, x, y));
    }
  }
  {
    int k = tid >> 3, c = tid & 7, sw = (k >> 4) * 2 + (k & 1);
    st_perm(sb + S_WH, k, c, sw, w1);
    st_perm(sb + S_WH + 8192, k, c, k & 7, w2);
  }
#pragma unroll
  for (int j = 0; j < 4; j++) ldsm4t(sb + S_W4 + ((lane >> 4) * 8 + (lane & 7)) * 128 + (((2 * j + ((lane >> 3) & 1)) ^ (lane & 7)) << 4), W4 + 4 * j);
  ldsm4t(sb + S_W4 + 2176 + (lane >> 3) * 32 + (lane & 1) * 16, wx);
  target = (target / NCTA + 1) * NCTA;
  if (tid == 15 * 32) bar_wait(target);
  TM(6);
  __syncthreads();
  TM(7);
  const int cnt = sm32[S_VAR / 4];
  uint2 r[RPT]; u32 gx[RPT], gy[RPT], rv[RPT];
#pragma unroll
  for (int k = 0; k < RPT; k++) r[k] = tid + k * NT < cnt ? __ldcg(&g_list[cta * CAP + tid + k * NT]) : make_uint2(0, ~0u);
  const u32 novf = __ldcg(&g_novf);
  const bool last = cnt > (RPT - 1) * NT;
#pragma unroll
  for (int k = 0; k < RPT; k++) {
    if (k < RPT - 1 || last) {
      u32 s = r[k].x & 0xffff;
      u32 x = sm32[(s * 3) >> 1], y = sm32[((s * 3) >> 1) + 1];
      uint2 pd = *(const uint2*)(smem + S_LP + (lane & 15) * 8 + ((r[k].x >> 9) & 0x7f80));
      rv[k] = ~0u;
      if (r[k].y != ~0u) rv[k] = atomicAdd((u32*)(smem + S_GC + prmt(pd.y, 0, 0x4442)), 128u);
      u32 sh = s << 4;
      x = __funnelshift_r(x, y, sh); y = __funnelshift_r(y, 0, sh);
      x = hsub2(pd.x, x); y = hsub2(pd.y, y);
      u32 qx = hmul2(x, x), qy = hmul2(y, y);
      gx[k] = x; gy[k] = pack2(blo(y), blo(qx) + bhi(qx) + blo(qy));
      r[k].y = prmt(r[k].y, pd.y, 0x7210);
      r[k].x = s;
    }
  }
  __syncthreads();
  TM(8);
  u32 ua, ub, pv;
  u32 Ac[8];
  {
    const u32 c = sm32[S_GC / 4 + lane] >> 7, cp = (c + 15) & ~15u;
    u32 d = min((__reduce_max_sync(~0u, cp) - cp) >> 4, 7u), eq = ~0u, lt = 0;
#pragma unroll
    for (int b = 2; b >= 0; b--) {
      u32 m = __ballot_sync(~0u, (d >> b) & 1);
      if ((d >> b) & 1) { lt |= eq & ~m; eq &= m; } else eq &= ~m;
    }
    const int rank = __popc(lt) + __popc(eq & ((1u << lane) - 1)), slot = rank < 16 ? 2 * rank : 63 - 2 * rank;
    sts32(sb + S_GC + 128 + slot * 4, cp);
    __syncwarp();
    u32 x = lds32(sb + S_GC + 128 + lane * 4);
#pragma unroll
    for (int o = 1; o < 32; o <<= 1) { u32 y = __shfl_up_sync(~0u, x, o); if (lane >= o) x += y; }
    x = __shfl_sync(~0u, x, slot);
    const u32 st = x - cp, st4 = st * 4;
#pragma unroll
    for (int k = 0; k < RPT; k++) {
      if (k < RPT - 1 || last) {
        u32 q = __shfl_sync(~0u, st4, rv[k]) + (rv[k] >> 5);
        if (rv[k] != ~0u) { sts32(sb + S_SO + q, r[k].x); sts32(sb + S_ED + q, r[k].y); sts64(sb + S_G + q * 2, gx[k], gy[k]); }
      }
    }
    int gsel = 2 * warp + (lane >> 4);
    u32 q = __shfl_sync(~0u, st + c, gsel) + (lane & 15), qe = __shfl_sync(~0u, x, gsel);
    if (q < qe) { sts32(sb + S_SO + q * 4, cta * 160 + gsel * 5); sts32(sb + S_ED + q * 4, 0x33000000u | (e0 + gsel * 4)); sts64(sb + S_G + q * 8, 0, 0); }
    u32 pk = (st >> 4) | ((x >> 4) << 10) | (lane * (6 << 20));
    ua = __reduce_max_sync(~0u, slot == 2 * warp ? pk : 0); ub = __reduce_max_sync(~0u, slot == 2 * warp + 1 ? pk : 0);
    int la = ua >> 20, lb = ub >> 20;
    int c8 = lane & 7, ra = (c8 & 3) == 3 ? 192 : la + c8 - (c8 >> 2), rb = (c8 & 3) == 3 ? 192 : lb + c8 - (c8 >> 2);
    u32 aa = sb + S_A + ra * 128 + (((lane >> 3) ^ (ra & 7)) << 4), ab = sb + S_A + rb * 128 + (((lane >> 3) ^ (rb & 7)) << 4);
    u32 X[8];
    ldsm4t(aa, Ac); ldsm4t(aa ^ 64, Ac + 4); ldsm4t(ab, X); ldsm4t(ab ^ 64, X + 4);
    pv = lds32(sb + S_LP + min((t & 2 ? lb : la) + g - (g >> 2), NPC - 1) * 128 + lane * 4);
    sts128(sb + S_X + warp * 1024 + lane * 16, make_uint4(X[0], X[1], X[2], X[3]));
    sts128(sb + S_X + warp * 1024 + 512 + lane * 16, make_uint4(X[4], X[5], X[6], X[7]));
  }
  if (tid == 14 * 32) bar_wait(target, &g_bar2[32]);
  if (novf) overflow_path(p, novf);
  __syncthreads();
  TM(9);
  ua = __reduce_max_sync(~0u, ua); ub = __reduce_max_sync(~0u, ub);
  const u32 stg = sb + S_STG + warp * 2 * STG;
  sts32(sb + S_ST + tid * 4, pv);
  if (lane == 0) sts128(sb + S_ST + 2048 + warp * 16, make_uint4(ua >> 20, novf, ub >> 20, 0));
  __syncwarp();
  const int q4 = lane >> 3, c8 = lane & 7;
  const u64 bptr = (u64)g_B | (c8 * 16), eptr = (u64)p.ea | ((lane & 1) * 16);
  u32 cpB0 = stg + q4 * 512 + ((c8 ^ (2 * q4)) << 4), cpB1 = cpB0 ^ 16;
  u32 cpE = stg + 2048 + q4 * 128 + ((4 * (((lane >> 1) ^ q4) & 1) + 2 * ((lane >> 2) & 1) + ((lane ^ (q4 >> 1)) & 1)) << 4);
  u32 ldB[4];
#pragma unroll
  for (int mt = 0; mt < 4; mt++) ldB[mt] = stg + (4 * (c8 >> 1) + 2 * (q4 & 1) + (c8 & 1)) * 128 + (((2 * mt + (q4 >> 1)) ^ c8) << 4);
  u32 ldE = stg + 2048 + (c8 >> 1) * 128 + ((4 * (((lane >> 4) ^ (c8 >> 1)) & 1) + 2 * (c8 & 1) + ((q4 ^ (c8 >> 2)) & 1)) << 4);
  u32 tlo = g < 3 ? 0x3fu << (8 * g) : 0, thi = (g >= 4 && g < 7) ? 0x3fu << (8 * (g - 4)) : 0;
  auto opq = [&](u32& v) { v = __shfl_sync(~0u, v, lane); };
  opq(cpB0); opq(cpB1); opq(cpE); opq(ldE); opq(tlo); opq(thi); opq(ldB[0]); opq(ldB[1]); opq(ldB[2]); opq(ldB[3]);
  const u32 to0 = (ua & 1023) * 64;
  u32 aSO = sb + S_SO + q4 * 16 + to0, aE1 = sb + S_ED + (lane >> 1) * 4 + to0, aE4 = sb + S_ED + t * 16 + to0, aG = sb + S_G + c8 * 16 + 2 * to0;
  auto issue = [&](uint4 so, u32 ed, u32 off, int pr) {
    asm volatile("{.reg .b64 a,b,c,d,e; .reg .pred q; setp.ne.s32 q,%10,0;\n"
      "mad.wide.u32 a,%3,128,%8; mad.wide.u32 b,%4,128,%8; mad.wide.u32 c,%5,128,%8; mad.wide.u32 d,%6,128,%8; mad.wide.u32 e,%7,32,%9;\n"
      "@q cp.async.cg.shared.global [%0],[a],16; @q cp.async.cg.shared.global [%1+128],[b],16;\n"
      "@q cp.async.cg.shared.global [%0+256],[c],16; @q cp.async.cg.shared.global [%1+384],[d],16;\n"
      "@q cp.async.cg.shared.global [%2],[e],16; cp.async.commit_group;}"
      ::"r"(cpB0 + off), "r"(cpB1 + off), "r"(cpE + off), "r"(so.x), "r"(so.y), "r"(so.z), "r"(so.w), "r"(DBG & 4 ? (ed & 0xffff) : ed & 0xffffffu), "l"(bptr), "l"(eptr),
        "r"(pr) : "memory");
  };
  int n = (ub & 1023) - (ua & 1023), c3 = 3 + (ub & 1023) - ((ub >> 10) & 1023);
#pragma unroll
  for (int k = 0; k < 2; k++) issue(lds128(aSO + k * 64), lds32(aE1 + k * 64), k * STG, n + 3 - c3 > k);
  u32 Sx[3], Sy[3] = {0, 0, 0}, ta, tb;
  auto build = [&](uint4 ed, u32& na, u32& nb, u32 vN) {
    na = prmt(tlo, thi, prmt(ed.x, ed.z, 0x73)); nb = prmt(tlo, thi, prmt(ed.y, ed.w, 0x73));
    na = g == 3 ? vN : na; nb = g == 7 ? vN : nb;
    ta = movm(na); tb = movm(nb);
  };
  Sx[2] = ldsm1t(aG);
  build(lds128(aE4), Sx[0], Sx[1], Sx[2]);
  float seg[4][4], pa[4];
  int gi = 0;
  auto reset = [&]() {
#pragma unroll
    for (int j = 0; j < 4; j++) { seg[j][0] = seg[j][1] = seg[j][2] = seg[j][3] = 0.f; pa[j] = 0.f; }
  };
  float x[4][4], y[4][4];
  u32 ca, cb;
  auto back = [&](int mt, u32 s0, u32 s1) {
    u32 m2 = pack2(silu_h(y[mt][0]), silu_h(y[mt][1])), m3 = pack2(silu_h(y[mt][2]), silu_h(y[mt][3]));
    u32 m0 = pack2(silu_h(x[mt][0]), silu_h(x[mt][1])), m1 = pack2(silu_h(x[mt][2]), silu_h(x[mt][3]));
    mma16(seg[mt], m0, m1, m2, m3, s0, s1);
    ca = hfma2l(m0, wx[mt], mt ? ca : 0x80008000u); cb = hfma2l(m2, wx[mt], mt ? cb : 0x80008000u);
    ca = hfma2h(m1, wx[mt], ca); cb = hfma2h(m3, wx[mt], cb);
  };
  auto body = [&](const u32 off, const u32 to, const u32* C, u32* O) {
    asm volatile("cp.async.wait_group 1;" ::: "memory");
    __syncwarp();
    u32 ef[4], b[4][4];
    auto front = [&](int mt) {
#pragma unroll
      for (int i = 0; i < 4; i++) { x[mt][i] = __uint_as_float(b[mt][i] * 65536u + 0x8000u); y[mt][i] = __uint_as_float(b[mt][i]); }
      mma16(y[mt], W4[4 * mt], W4[4 * mt + 1], W4[4 * mt + 2], W4[4 * mt + 3], ef[2], ef[3]);
      mma16(x[mt], W4[4 * mt], W4[4 * mt + 1], W4[4 * mt + 2], W4[4 * mt + 3], ef[0], ef[1]);
      mma8(y[mt], Ac[2 * mt], Ac[2 * mt + 1], tb);
      mma8(x[mt], Ac[2 * mt], Ac[2 * mt + 1], ta);
    };
    ldsm4(ldE + off, ef);
    ldsm4t(ldB[0] + off, b[0]);
    ldsm4t(ldB[1] + off, b[1]);
    uint4 so = lds128(aSO + to + 128);
    u32 e1 = lds32(aE1 + to + 128);
    back(3, O[0], O[1]);
    u32 keep = g < 4 ? ca : cb, send = g < 4 ? cb : ca;
    front(0);
    ldsm4t(ldB[2] + off, b[2]);
    ldsm4t(ldB[3] + off, b[3]);
    front(1);
    issue(so, e1, off, DBG & 1 ? 0 : to ? n > c3 : n >= c3);
    keep = hadd2(keep, __shfl_xor_sync(~0u, send, 16));
    back(0, C[0], C[1]);
    keep = hadd2(keep, __shfl_xor_sync(~0u, keep, 8));
    front(2);
    keep = hadd2(keep, __shfl_xor_sync(~0u, keep, 4));
    back(1, C[0], C[1]);
    mma8(pa, O[0], O[1], hmul2(keep, O[2]));
    front(3);
    uint4 ed = lds128(aE4 + to + 64);
    O[2] = ldsm1t(aG + 2 * to + 128);
    build(ed, O[0], O[1], O[2]);
    back(2, C[0], C[1]);
  };
  auto fin = [&]() {
    uint4 gv = lds128(sb + S_ST + 2048 + warp * 16);
    gi = gv.w;
    n0 = node_of(gv.x, g, cta); n1 = node_of(gv.z, g, cta);
    load_h(p, gi ? n0 : -1, gi ? n1 : -1, t, h0, h1);
    back(3, n ? Sx[0] : Sy[0], n ? Sx[1] : Sy[1]);
    u32 keep = g < 4 ? ca : cb, send = g < 4 ? cb : ca;
    keep = hadd2(keep, __shfl_xor_sync(~0u, send, 16));
    keep = hadd2(keep, __shfl_xor_sync(~0u, keep, 8));
    keep = hadd2(keep, __shfl_xor_sync(~0u, keep, 4));
    mma8(pa, n ? Sx[0] : Sy[0], n ? Sx[1] : Sy[1], hmul2(keep, n ? Sx[2] : Sy[2]));
#pragma unroll
    for (int j = 0; j < 3; j++) { if (n) Sx[j] = 0; else Sy[j] = 0; }
    __syncwarp();
    sts32(sb + S_ST + 2048 + warp * 16 + 12, 1);
    const u32 pv = lds32(sb + S_ST + (tid ^ (2 * gi)) * 4);
    const int nd = gi ? n1 : n0;
    if (gv.y) {
      int na = __shfl_sync(~0u, nd, 8 * t), nb = __shfl_sync(~0u, nd, 8 * t + 4);
#pragma unroll
      for (int mt = 0; mt < 4; mt++) {
        if (na >= 0) { seg[mt][0] += 0.5f * __ldcg(&g_acc[na * 68 + 16 * mt + g]); seg[mt][2] += 0.5f * __ldcg(&g_acc[na * 68 + 16 * mt + 8 + g]); }
        if (nb >= 0) { seg[mt][1] += 0.5f * __ldcg(&g_acc[nb * 68 + 16 * mt + g]); seg[mt][3] += 0.5f * __ldcg(&g_acc[nb * 68 + 16 * mt + 8 + g]); }
      }
      if (nd >= 0 && t < 2) { pa[0] += 0.5f * __ldcg(&g_acc[nd * 68 + 64 + 2 * t]); pa[1] += 0.5f * __ldcg(&g_acc[nd * 68 + 65 + 2 * t]); }
    }
    float u0 = pa[0] + __shfl_xor_sync(~0u, pa[2], 2), u1 = pa[1] + __shfl_xor_sync(~0u, pa[3], 2);
    if (nd >= 0 && t < 2) {
      u32 o = hadd2(pv, pack2(2.f * u0, 2.f * u1));
      unsigned short* po = (unsigned short*)p.out + NN * 64 + nd * 3 + 2 * t;
      po[0] = o & 0xffff;
      if (t == 0) po[1] = o >> 16;
    }
    {
      const u32 xa = sb + S_X + warp * 1024 + lane * 16;
      uint4 x0 = lds128(xa), x1 = lds128(xa + 512);
      Ac[0] = x0.x; Ac[1] = x0.y; Ac[2] = x0.z; Ac[3] = x0.w; Ac[4] = x1.x; Ac[5] = x1.y; Ac[6] = x1.z; Ac[7] = x1.w;
      u32 X[8];
#pragma unroll
      for (int mt = 0; mt < 4; mt++) {
        X[2 * mt] = movm(pack2(2.f * seg[mt][0], 2.f * seg[mt][1]));
        X[2 * mt + 1] = movm(pack2(2.f * seg[mt][2], 2.f * seg[mt][3]));
      }
      sts128(xa, make_uint4(X[0], X[1], X[2], X[3])); sts128(xa + 512, make_uint4(X[4], X[5], X[6], X[7]));
    }
  };
  n *= 2;
#pragma unroll 1
  do {
    reset();
    ca = cb = 0;
#pragma unroll
    for (int j = 0; j < 4; j++) x[3][j] = y[3][j] = 0.f;
    n = __reduce_max_sync(~0u, n);
    const bool odd = n & 1;
    n >>= 1;
    if (n > (int)odd) {
      if (odd) { body(STG, 64, Sy, Sx); aSO += 128; aE1 += 128; aE4 += 128; aG += 256; n -= 2; }
      while (n) {
        body(0, 0, Sx, Sy);
        if (n == 1) break;
        body(STG, 64, Sy, Sx);
        aSO += 128; aE1 += 128; aE4 += 128; aG += 256; n -= 2;
      }
    }
    fin();
    n = 3 * n + 6 - 2 * c3; c3 = 3;
  } while (!gi);
  TM(10);
  {
    u32 X[8];
    *(uint4*)X = lds128(sb + S_X + warp * 1024 + lane * 16); *(uint4*)(X + 4) = lds128(sb + S_X + warp * 1024 + 512 + lane * 16);
    float acc[8][4];
#pragma unroll
    for (int j = 0; j < 8; j++) acc[j][0] = acc[j][1] = acc[j][2] = acc[j][3] = 0.f;
#pragma unroll
    for (int s = 0; s < 4; s++) {
      u32 row = sb + S_WH + 8192 + (16 * s + (lane & 15)) * 128;
#pragma unroll
      for (int j = 0; j < 8; j += 2) {
        u32 w[4]; ldsm4t(row + (((j + (lane >> 4)) ^ c8) << 4), w);
        mma16(acc[j], Ac[2 * s], X[2 * s], Ac[2 * s + 1], X[2 * s + 1], w[0], w[1]);
        mma16(acc[j + 1], Ac[2 * s], X[2 * s], Ac[2 * s + 1], X[2 * s + 1], w[2], w[3]);
      }
    }
    gemm_perm(acc, h0, h1, sb + S_WH, lane);
    u32* a = (u32*)h0; u32* c = (u32*)h1;
#pragma unroll
    for (int j = 0; j < 8; j++) {
      a[j] = hadd2(a[j], pack2(silu_h(0.5f * acc[j][0]), silu_h(0.5f * acc[j][1])));
      c[j] = hadd2(c[j], pack2(silu_h(0.5f * acc[j][2]), silu_h(0.5f * acc[j][3])));
    }
    uint4* o = (uint4*)p.out;
    if (n0 >= 0) { o[n0 * 8 + 2 * t] = h0[0]; o[n0 * 8 + 2 * t + 1] = h0[1]; }
    if (n1 >= 0) { o[n1 * 8 + 2 * t] = h1[0]; o[n1 * 8 + 2 * t + 1] = h1[1]; }
  }
  TM(11);
}

__global__ void fb_zero() { for (int i = blockIdx.x * blockDim.x + threadIdx.x; i < NN * 68; i += gridDim.x * blockDim.x) g_acc[i] = 0.f; }
__global__ void fb_edge(const __grid_constant__ P p) { for (int e = blockIdx.x * 8 + (threadIdx.x >> 5); e < NE; e += gridDim.x * 8) slow_edge(p, e, threadIdx.x & 31); }
__global__ void fb_node(const P p) {
  int n = blockIdx.x, f = threadIdx.x;
  float x = 0.f;
  for (int k = 0; k < 64; k++) x += b2f(p.h[n * 64 + k]) * b2f(p.wh[k * 64 + f]) + rbf(g_acc[n * 68 + k]) * b2f(p.wh[(64 + k) * 64 + f]);
  p.out[n * 64 + f] = __float2bfloat16_rn(b2f(p.h[n * 64 + f]) + rbf(silu_h(0.5f * x)));
  if (f < 3) p.out[NN * 64 + n * 3 + f] = __float2bfloat16_rn(b2f(p.pos[n * 3 + f]) + rbf(g_acc[n * 68 + 64 + f]));
}

extern "C" void kernel_launch(void* const* d_in, const int* in_sizes, int n_in, void* d_out, int out_size) {
  static int mode = -1;
  if (mode < 0) {
    int dev = 0, sms = 0, occ = 0;
    cudaGetDevice(&dev);
    cudaDeviceGetAttribute(&sms, cudaDevAttrMultiProcessorCount, dev);
    cudaError_t e = cudaFuncSetAttribute(egnn_kernel, cudaFuncAttributeMaxDynamicSharedMemorySize, S_END);
    if (e == cudaSuccess) e = cudaOccupancyMaxActiveBlocksPerMultiprocessor(&occ, egnn_kernel, NT, S_END);
    mode = (e == cudaSuccess && occ * sms >= NCTA) ? 1 : 0;
    cudaGetLastError();
  }
  P p;
  p.h = (const __nv_bfloat16*)d_in[0]; p.pos = (const __nv_bfloat16*)d_in[1]; p.ea = (const __nv_bfloat16*)d_in[2];
  p.src = (const int*)d_in[3]; p.dst = (const int*)d_in[4];
  p.we = (const __nv_bfloat16*)d_in[5]; p.wx = (const __nv_bfloat16*)d_in[6]; p.wh = (const __nv_bfloat16*)d_in[7];
  p.out = (__nv_bfloat16*)d_out;
  if (mode == 1) {
    egnn_kernel<<<NCTA, NT, S_END>>>(p);
  } else {
    fb_zero<<<512, 256>>>(); fb_edge<<<2048, 256>>>(p); fb_node<<<NN, 64>>>(p);
  }
}
```

```cpp
#include <cuda_runtime.h>
#include <cuda_bf16.h>
#include <stdint.h>

#pragma nv_diag_suppress 549
typedef unsigned int u32;
typedef unsigned long long u64;
#define DEVI __device__ __forceinline__

constexpr int NN = 25000, NE = 800000;
constexpr int NCTA = 132, NT = 512, NPC = 190, CHUNK = 6064, CAP = 6656, MAXPOS = 7136;
constexpr int RPT = 13;
constexpr int S_POS = 0, S_REC = 150016, S_A = S_REC, S_LP = S_A + 193 * 128;
constexpr int S_CNT = S_REC + (CHUNK + 3 * NCTA) * 8, S_DEL = S_CNT + 528, S_GB = S_DEL + 528, S_MB = S_GB + 528, S_GC = 199056, S_VAR = S_GC + 256;
constexpr int S_X = 199680, S_WH = S_X + 16384, S_W1 = S_WH, S_W2 = S_W1 + 8192, S_END = S_WH + 16384, S_W4 = S_X + 5120;
constexpr int S_SO = 0, S_ED = MAXPOS * 4, S_G = MAXPOS * 8, S_STG = MAXPOS * 16, STG = 2560, S_ST = S_STG + 32 * STG;
static_assert(S_LP + NPC * 128 <= S_GC && S_VAR + 16 <= S_X && S_MB + 8 <= S_W4 && S_ST + 2048 + 256 <= S_GC && S_END <= 232448, "smem");

__device__ __align__(128) uint2 g_list[NCTA * CAP];
__device__ __align__(128) uint4 g_B[NN * 8];
__device__ u32 g_cnt[NCTA * 8];
__device__ u32 g_bar, g_novf, g_bar2[64];
__device__ u32 g_ovf[NE];
__device__ float g_acc[NN * 68];

DEVI u32 lds32(u32 a) { u32 v; asm volatile("ld.shared.u32 %0,[%1];" : "=r"(v) : "r"(a)); return v; }
DEVI uint2 lds64(u32 a) { uint2 v; asm volatile("ld.shared.v2.u32 {%0,%1},[%2];" : "=r"(v.x), "=r"(v.y) : "r"(a)); return v; }
DEVI uint4 lds128(u32 a) { uint4 v; asm volatile("ld.shared.v4.u32 {%0,%1,%2,%3},[%4];" : "=r"(v.x), "=r"(v.y), "=r"(v.z), "=r"(v.w) : "r"(a)); return v; }
DEVI void sts32(u32 a, u32 v) { asm volatile("st.shared.u32 [%0],%1;" ::"r"(a), "r"(v) : "memory"); }
DEVI void sts64(u32 a, u32 x, u32 y) { asm volatile("st.shared.v2.u32 [%0],{%1,%2};" ::"r"(a), "r"(x), "r"(y) : "memory"); }
DEVI void sts128(u32 a, uint4 v) { asm volatile("st.shared.v4.u32 [%0],{%1,%2,%3,%4};" ::"r"(a), "r"(v.x), "r"(v.y), "r"(v.z), "r"(v.w) : "memory"); }
DEVI u32 atoms_inc(u32 a) { u32 v; asm volatile("atom.shared.add.u32 %0,[%1],1;" : "=r"(v) : "r"(a) : "memory"); return v; }
DEVI void ldsm4(u32 a, u32* r) { asm volatile("ldmatrix.sync.aligned.m8n8.x4.shared.b16 {%0,%1,%2,%3},[%4];" : "=r"(r[0]), "=r"(r[1]), "=r"(r[2]), "=r"(r[3]) : "r"(a)); }
DEVI void ldsm4t(u32 a, u32* r) { asm volatile("ldmatrix.sync.aligned.m8n8.x4.trans.shared.b16 {%0,%1,%2,%3},[%4];" : "=r"(r[0]), "=r"(r[1]), "=r"(r[2]), "=r"(r[3]) : "r"(a)); }
DEVI u32 ldsm1t(u32 a) { u32 r; asm volatile("ldmatrix.sync.aligned.m8n8.x1.trans.shared.b16 {%0},[%1];" : "=r"(r) : "r"(a)); return r; }
DEVI u32 movm(u32 a) { u32 r; asm("movmatrix.sync.aligned.m8n8.trans.b16 %0,%1;" : "=r"(r) : "r"(a)); return r; }
DEVI void mma16(float* c, u32 a0, u32 a1, u32 a2, u32 a3, u32 b0, u32 b1) {
  asm("mma.sync.aligned.m16n8k16.row.col.f32.bf16.bf16.f32 {%0,%1,%2,%3},{%4,%5,%6,%7},{%8,%9},{%0,%1,%2,%3};"
      : "+f"(c[0]), "+f"(c[1]), "+f"(c[2]), "+f"(c[3]) : "r"(a0), "r"(a1), "r"(a2), "r"(a3), "r"(b0), "r"(b1));
}
DEVI void mma8(float* c, u32 a0, u32 a1, u32 b0) {
  asm("mma.sync.aligned.m16n8k8.row.col.f32.bf16.bf16.f32 {%0,%1,%2,%3},{%4,%5},{%6},{%0,%1,%2,%3};"
      : "+f"(c[0]), "+f"(c[1]), "+f"(c[2]), "+f"(c[3]) : "r"(a0), "r"(a1), "r"(b0));
}
DEVI u32 pack2(float lo, float hi) { u32 r; asm("cvt.rn.bf16x2.f32 %0,%1,%2;" : "=r"(r) : "f"(hi), "f"(lo)); return r; }
DEVI u32 pack2z(float lo, float hi) { u32 r; asm("cvt.rz.bf16x2.f32 %0,%1,%2;" : "=r"(r) : "f"(hi), "f"(lo)); return r; }
DEVI u32 hfma2l(u32 a, u32 b, u32 c) { u32 r; asm("{.reg .b16 l,h; .reg .b32 d; mov.b32 {l,h},%2; mov.b32 d,{l,l}; fma.rn.bf16x2 %0,%1,d,%3;}" : "=r"(r) : "r"(a), "r"(b), "r"(c)); return r; }
DEVI u32 hfma2h(u32 a, u32 b, u32 c) { u32 r; asm("{.reg .b16 l,h; .reg .b32 d; mov.b32 {l,h},%2; mov.b32 d,{h,h}; fma.rn.bf16x2 %0,%1,d,%3;}" : "=r"(r) : "r"(a), "r"(b), "r"(c)); return r; }
DEVI int node_of(int l0, int g, int cta) { int l = l0 + g - (g >> 2), n = cta * NPC + l; return ((g & 3) == 3 || l >= NPC || n >= NN) ? -1 : n; }
DEVI u32 hmul2(u32 a, u32 b) { u32 r; asm("mul.rn.bf16x2 %0,%1,%2;" : "=r"(r) : "r"(a), "r"(b)); return r; }
DEVI u32 hadd2(u32 a, u32 b) { u32 r; asm("add.rn.bf16x2 %0,%1,%2;" : "=r"(r) : "r"(a), "r"(b)); return r; }
DEVI u32 hsub2(u32 a, u32 b) { u32 r; asm("sub.rn.bf16x2 %0,%1,%2;" : "=r"(r) : "r"(a), "r"(b)); return r; }
DEVI u32 hfma2(u32 a, u32 b, u32 c) { u32 r; asm("fma.rn.bf16x2 %0,%1,%2,%3;" : "=r"(r) : "r"(a), "r"(b), "r"(c)); return r; }
DEVI u32 prmt(u32 a, u32 b, u32 c) { u32 r; asm("prmt.b32 %0,%1,%2,%3;" : "=r"(r) : "r"(a), "r"(b), "r"(c)); return r; }
DEVI float blo(u32 v) { return __uint_as_float(v << 16); }
DEVI float bhi(u32 v) { return __uint_as_float(v & 0xffff0000u); }
DEVI float silu_h(float hx) { float t; asm("tanh.approx.f32 %0,%1;" : "=f"(t) : "f"(hx)); return fmaf(hx, t, hx); }
DEVI void cp16(u32 s, const void* g) { asm volatile("cp.async.cg.shared.global [%0],[%1],16;" ::"r"(s), "l"(g) : "memory"); }
DEVI const void* madw(u32 a, u32 b, const void* c) { const void* r; asm("mad.wide.u32 %0,%1,%2,%3;" : "=l"(r) : "r"(a), "r"(b), "l"(c)); return r; }
DEVI u32 ld_acq(const u32* p) { u32 v; asm volatile("ld.acquire.gpu.global.u32 %0,[%1];" : "=r"(v) : "l"(p) : "memory"); return v; }
DEVI float b2f(__nv_bfloat16 x) { return __bfloat162float(x); }
DEVI float rbf(float x) { return __bfloat162float(__float2bfloat16_rn(x)); }

DEVI u32 bar_arrive() {
  __threadfence();
  u32 t = atomicAdd(&g_bar, 1u);
  return (t / NCTA + 1) * NCTA;
}
DEVI void bar_wait(u32 target, const u32* bar = &g_bar) {
  u32 it = 0;
  while ((int)(ld_acq(bar) - target) < 0) { if (++it > (1u << 26)) __trap(); }
}
DEVI void grid_sync() {
  __syncthreads();
  if (threadIdx.x == 0) bar_wait(bar_arrive());
  __syncthreads();
}

struct P {
  const __nv_bfloat16 *h, *pos, *ea; const int *src, *dst; const __nv_bfloat16 *we, *wx, *wh; __nv_bfloat16* out;
};

__device__ __noinline__ void slow_edge(const P& p, int e, int lane) {
  int s = p.src[e], d = p.dst[e];
  float df[3], d2 = 0.f;
  for (int c = 0; c < 3; c++) { df[c] = rbf(b2f(p.pos[d * 3 + c]) - b2f(p.pos[s * 3 + c])); d2 += rbf(df[c] * df[c]); }
  d2 = rbf(d2);
  const u32* w = (const u32*)p.we + lane;
  float x0 = d2 * blo(w[128 * 32]), x1 = d2 * bhi(w[128 * 32]);
  for (int k = 0; k < 64; k++) {
    float a = b2f(p.h[d * 64 + k]), b = b2f(p.h[s * 64 + k]);
    u32 wa = w[k * 32], wb = w[(64 + k) * 32];
    x0 += a * blo(wa) + b * blo(wb); x1 += a * bhi(wa) + b * bhi(wb);
  }
  for (int k = 0; k < 16; k++) { float a = b2f(p.ea[(size_t)e * 16 + k]); u32 wa = w[(129 + k) * 32]; x0 += a * blo(wa); x1 += a * bhi(wa); }
  float m0 = rbf(silu_h(0.5f * x0)), m1 = rbf(silu_h(0.5f * x1));
  float cs = m0 * b2f(p.wx[2 * lane]) + m1 * b2f(p.wx[2 * lane + 1]);
  for (int o = 16; o; o >>= 1) cs += __shfl_xor_sync(~0u, cs, o);
  cs = rbf(cs);
  atomicAdd(&g_acc[d * 68 + 2 * lane], m0); atomicAdd(&g_acc[d * 68 + 2 * lane + 1], m1);
  if (lane < 3) atomicAdd(&g_acc[d * 68 + 64 + lane], rbf((lane == 0 ? df[0] : lane == 1 ? df[1] : df[2]) * cs));
}

__device__ __noinline__ void overflow_path(const P& p, u32 novf) {
  for (int i = blockIdx.x * NT + threadIdx.x; i < NN * 68; i += NCTA * NT) g_acc[i] = 0.f;
  grid_sync();
  if (blockIdx.x == 0 && threadIdx.x == 0) g_novf = 0;
  for (u32 i = blockIdx.x * 16 + (threadIdx.x >> 5); i < novf; i += NCTA * 16) slow_edge(p, __ldcg(&g_ovf[i]), threadIdx.x & 31);
  grid_sync();
}

DEVI void gemm_perm(float (*acc)[4], const uint4* h0, const uint4* h1, u32 wbase, int lane) {
  const int r = lane & 7, b = (lane >> 3) & 1, jo = lane >> 4;
  const u32* a = (const u32*)h0; const u32* c = (const u32*)h1;
#pragma unroll
  for (int s = 0; s < 4; s++) {
    u32 row = wbase + (32 * (s >> 1) + 8 * (r >> 1) + 4 * (s & 1) + 2 * b + (r & 1)) * 128;
#pragma unroll
    for (int j = 0; j < 8; j += 2) {
      u32 w[4]; ldsm4t(row + (((j + jo) ^ r) << 4), w);
      mma16(acc[j], a[2 * s], c[2 * s], a[2 * s + 1], c[2 * s + 1], w[0], w[1]);
      mma16(acc[j + 1], a[2 * s], c[2 * s], a[2 * s + 1], c[2 * s + 1], w[2], w[3]);
    }
  }
}
DEVI void load_h(const P& p, int n0, int n1, int t, uint4* h0, uint4* h1) {
  const uint4 z = make_uint4(0, 0, 0, 0);
  const uint4* hp = (const uint4*)p.h;
  h0[0] = n0 >= 0 ? __ldg(hp + n0 * 8 + t) : z; h0[1] = n0 >= 0 ? __ldg(hp + n0 * 8 + t + 4) : z;
  h1[0] = n1 >= 0 ? __ldg(hp + n1 * 8 + t) : z; h1[1] = n1 >= 0 ? __ldg(hp + n1 * 8 + t + 4) : z;
}
DEVI void st_perm(u32 base, int k, int c, int sw, uint4 v) {
  u32 a = base + k * 128 + (c & 3) * 4; int j = c & 4;
  sts32(a + (((j) ^ sw) << 4), v.x); sts32(a + (((j + 1) ^ sw) << 4), v.y);
  sts32(a + (((j + 2) ^ sw) << 4), v.z); sts32(a + (((j + 3) ^ sw) << 4), v.w);
}

constexpr int NG = 4;
constexpr int PB = 2, PC = 5, PD = 11;
#define TM(i)

__global__ void __launch_bounds__(NT, 1) egnn_kernel(const __grid_constant__ P p) {
  extern __shared__ __align__(128) unsigned char smem[];
  const u32 sb = (u32)__cvta_generic_to_shared(smem);
  const int tid = threadIdx.x, lane = tid & 31, warp = tid >> 5, cta = blockIdx.x;
  const int g = lane >> 2, t = lane & 3;
  TM(0);
  u32* const sm32 = (u32*)smem;
  auto pos_tma = [&](int k0, int k1) {
    if (tid == 64) {
      for (int k = k0; k < k1; k++) {
        int kk = (k + cta) % 5;
        asm volatile("cp.async.bulk.shared::cluster.global.mbarrier::complete_tx::bytes [%0],[%1],%2,[%3];"
                     ::"r"(sb + S_POS + kk * 30000), "l"((const char*)p.pos + kk * 30000), "r"(30000), "r"(sb + S_MB) : "memory");
      }
    }
  };
  if (tid == 64) {
    asm volatile("mbarrier.init.shared.b64 [%0],1;" ::"r"(sb + S_MB) : "memory");
    asm volatile("fence.mbarrier_init.release.cluster;" ::: "memory");
    asm volatile("mbarrier.arrive.expect_tx.shared.b64 _,[%0],%1;" ::"r"(sb + S_MB), "r"(NN * 6) : "memory");
  }
  pos_tma(0, 5);
  const int e0 = cta * CHUNK, ne4 = (min(NE, e0 + CHUNK) - e0) >> 2;
  const bool v3 = tid + 2 * NT < ne4;
  int4 dv[3], sv[3];
#pragma unroll
  for (int k = 0; k < 3; k++) if (k < 2 || v3) dv[k] = __ldcs((const int4*)(p.dst + e0) + tid + k * NT);
#pragma unroll
  for (int k = 0; k < 3; k++) if (k < 2 || v3) sv[k] = __ldcs((const int4*)(p.src + e0) + tid + k * NT);
  u32 target = 0;
  if (tid < NCTA) sm32[S_CNT / 4 + tid] = 0;
  if (tid >= 14 * 32 && lane == 0) target = __ldcg(warp == 15 ? &g_bar : &g_bar2[32]);
  uint4 h0[2], h1[2];
  int n0, n1;
  {
    int l0 = warp * 16 + g;
    n0 = cta * NPC + l0; n1 = n0 + 8;
    if (l0 >= NPC || n0 >= NN) n0 = -1;
    if (l0 + 8 >= NPC || n1 >= NN) n1 = -1;
  }
  if (tid >= 239) {
    asm volatile("prefetch.global.L2 [%0];" ::"l"(tid >= 384 ? (const char*)p.wh + (tid - 384) * 128 : (const char*)p.we + (tid - 239) * 128));
  }
  __syncthreads();
  TM(1);
  u32 rec[12], rk[12];
#pragma unroll
  for (int k = 0; k < 12; k++) {
    if (k < 8 || v3) {
      u32 d = ((const int*)dv)[k], o = __umulhi(d, 22605092u);
      rk[k] = atomicAdd(sm32 + S_CNT / 4 + o, 8u);
      rec[k] = (d + o * (256 - NPC)) << 16;
    }
  }
  uint4 w1 = __ldg((const uint4*)p.we + tid), w2 = __ldg((const uint4*)p.we + 512 + tid);
  load_h(p, n0, n1, t, h0, h1);
  if (warp >= 12) h0[0] = __ldg((const uint4*)p.we + 129 * 8 + (tid - 384));
  if (warp == 12 && lane < 16) h0[1] = __ldg(lane < 8 ? (const uint4*)p.we + 128 * 8 + lane : (const uint4*)p.wx + (lane - 8));
  __syncthreads();
  TM(2);
  u32 gb[2], of[2], cn[2] = {0, 0};
  if (warp >= 13) {
    const int j = tid - 13 * 32;
    if (j < NCTA / 2) { uint2 c = lds64(sb + S_CNT + j * 8); cn[0] = c.x; cn[1] = c.y; }
    const u32 c0 = (cn[0] + 31) & ~31u, c1 = (cn[1] + 31) & ~31u;
    if (j < NCTA / 2) { gb[0] = atomicAdd(&g_cnt[j * 16], (c0 >> 3) + (1u << 24)); gb[1] = atomicAdd(&g_cnt[j * 16 + 8], (c1 >> 3) + (1u << 24)); }
    u32 pre = 0;
#pragma unroll
    for (int k = 0; k < 2; k++) if (k < warp - 13) { uint2 v = lds64(sb + S_CNT + (k * 32 + lane) * 8); pre += ((v.x + 31) & ~31u) + ((v.y + 31) & ~31u); }
    pre = __reduce_add_sync(~0u, pre);
    u32 x = c0 + c1;
#pragma unroll
    for (int o = 1; o < 32; o <<= 1) { u32 y = __shfl_up_sync(~0u, x, o); if (lane >= o) x += y; }
    of[1] = pre + x - c1; of[0] = of[1] - c0;
    if (j < NCTA / 2) sts64(sb + S_DEL + j * 8, of[0], of[1]);
#pragma unroll
    for (int k = 0; k < 2; k++) for (u32 i = cn[k]; i & 31; i += 8) sts64(sb + S_REC + of[k] + i, 0, ~0u);
  }
  __syncthreads();
  TM(3);
#pragma unroll
  for (int k = 0; k < 12; k++) if (k < 8 || v3) rk[k] += sm32[S_DEL / 4 + (rec[k] >> 24)];
#pragma unroll
  for (int k = 0; k < 12; k++) if (k < 8 || v3) sts64(sb + S_REC + rk[k], rec[k] | ((const int*)sv)[k], e0 + (tid + (k >> 2) * NT) * 4 + (k & 3));
  {
    int k = tid >> 3, c = tid & 7, sw = ((k >> 3) & 3) * 2 + (k & 1);
    sts128(sb + S_W1 + k * 128 + ((c ^ sw) << 4), w1);
    st_perm(sb + S_W2, k, c, sw, w2);
    const u32 hf = 0x3f003f00u;
    if (warp >= 12) sts128(sb + S_W4 + (k - 48) * 128 + ((c ^ (k & 7)) << 4), make_uint4(hmul2(h0[0].x, hf), hmul2(h0[0].y, hf), hmul2(h0[0].z, hf), hmul2(h0[0].w, hf)));
    if (warp == 12 && lane < 16) sts128(sb + S_W4 + 2048 + lane * 16, h0[1]);
  }
  if (warp >= 13 && tid - 13 * 32 < NCTA / 2) sts64(sb + S_GB + (tid - 13 * 32) * 8, gb[0], gb[1]);
  asm volatile("fence.proxy.async.shared::cta;" ::: "memory");
  __syncthreads();
  TM(4);
  auto pf_ea = [&](int w0, int w1) {
    if (lane == 0 && warp >= w0 && warp < w1) {
      int nb = 2 * min(CHUNK, NE - e0);
      asm volatile("cp.async.bulk.prefetch.L2.global [%0],%1;" ::"l"((const char*)p.ea + (size_t)e0 * 32 + warp * nb), "r"(nb) : "memory");
    }
  };
  if (lane < (warp < 12 ? NG : (132 - 12 * NG) / 4)) {
    const u32 o = lane + (warp < 12 ? warp * NG : 12 * NG + (warp - 12) * ((132 - 12 * NG) / 4)), c = sm32[S_CNT / 4 + o], src = sb + S_REC + sm32[S_DEL / 4 + o];
    const u32 base = min((sm32[S_GB / 4 + o] & 0xffffffu) * 8, CAP * 8u), fit = min((c + 31) & ~31u, CAP * 8 - base);
    if (fit) asm volatile("cp.async.bulk.global.shared::cta.bulk_group [%0],[%1],%2; cp.async.bulk.commit_group;"
                          ::"l"((char*)g_list + o * (CAP * 8) + base), "r"(src), "r"(fit) : "memory");
    if (fit < c) {
      u32 q = atomicAdd(&g_novf, (c - fit) >> 3);
      for (u32 i = fit; i < c; i += 8) g_ovf[q++] = lds32(src + i + 4);
      __threadfence();
    }
  }
  u32 W4[16], wx[4], o0[8], o1[8];
  w1 = __ldg((const uint4*)p.wh + tid); w2 = __ldg((const uint4*)p.wh + 512 + tid);
  if (warp < 12) {
    float acc[8][4];
#pragma unroll
    for (int j = 0; j < 8; j++) acc[j][0] = acc[j][1] = acc[j][2] = acc[j][3] = 0.f;
    gemm_perm(acc, h0, h1, sb + S_W2, lane);
#pragma unroll
    for (int j = 0; j < 8; j++) { o0[j] = pack2z(0.5f * acc[j][0], 0.5f * acc[j][1]); o1[j] = pack2z(0.5f * acc[j][2], 0.5f * acc[j][3]); }
  }
  asm volatile("cp.async.bulk.wait_group 0; fence.proxy.async.global;" ::: "memory");
  __syncthreads();
  TM(5);
  if (tid == 15 * 32) asm volatile("red.relaxed.gpu.global.add.u32 [%0],1;" ::"l"(&g_bar) : "memory");
  if (warp < 12) {
    if (n0 >= 0) { g_B[n0 * 8 + t] = make_uint4(o0[0], o0[1], o0[2], o0[3]); g_B[n0 * 8 + t + 4] = make_uint4(o0[4], o0[5], o0[6], o0[7]); }
    if (n1 >= 0) { g_B[n1 * 8 + t] = make_uint4(o1[0], o1[1], o1[2], o1[3]); g_B[n1 * 8 + t + 4] = make_uint4(o1[4], o1[5], o1[6], o1[7]); }
  }
  {
    u32 done, it = 0;
    do {
      asm volatile("{.reg .pred q; mbarrier.try_wait.parity.shared.b64 q,[%1],0; selp.u32 %0,1,0,q;}" : "=r"(done) : "r"(sb + S_MB) : "memory");
      if (++it > (1u << 24)) __trap();
    } while (!done);
  }
#pragma unroll
  for (int k = 0; k < 2; k++) {
    int l = ((NT - 1 - tid) >> 2) + k * 128, n = min(cta * NPC + l, NN - 1);
    if (l < NPC) {
      u32 x = sm32[(n * 3) >> 1], y = sm32[((n * 3) >> 1) + 1];
      if (n & 1) { x = __funnelshift_r(x, y, 16); y >>= 16; }
      u32 grp = (l * 171) >> 10, sl = l - grp * 6;
      sl += sl >= 3;
      y = (y & 0xffff) | (grp << 18) | (sl << 28) | (3u << 24);
      u32 a = sb + S_LP + l * 128 + t * 16 + (l & 1) * 64;
      sts128(a, make_uint4(x, y, x, y)); sts128(a ^ 64, make_uint4(x, y, x, y));
    }
  }
  if (warp < 12) {
    float acc[8][4];
#pragma unroll
    for (int j = 0; j < 8; j++) acc[j][0] = acc[j][1] = acc[j][2] = acc[j][3] = 0.f;
    gemm_perm(acc, h0, h1, sb + S_W1, lane);
#pragma unroll
    for (int j = 0; j < 8; j++) {
      u32 a = sb + S_A + (warp * 16 + g) * 128 + ((j ^ g) << 4) + t * 4;
      sts32(a, pack2(acc[j][0], acc[j][1])); sts32(a + 1024, pack2(acc[j][2], acc[j][3]));
    }
  } else if (warp == 12) {
    sm32[S_GC / 4 + lane] = lane;
    if (lane == 0) asm volatile("mbarrier.init.shared.b64 [%0],16;" ::"r"(sb + S_VAR + 8) : "memory");
    sm32[(S_A + 192 * 128) / 4 + lane] = hmul2(sm32[(S_W4 + 2048) / 4 + lane], 0x3f003f00u);
  } else if (tid == 13 * 32) {
    u32 v, it = 0;
    while (((v = ld_acq(&g_cnt[cta * 8])) >> 24) != NCTA) { if (++it > (1u << 26)) __trap(); }
    g_cnt[cta * 8] = 0;
    sm32[S_VAR / 4] = min(v & 0xffffffu, (u32)CAP);
  }
#pragma unroll
  for (int j = 0; j < 4; j++) ldsm4t(sb + S_W4 + ((lane >> 4) * 8 + (lane & 7)) * 128 + (((2 * j + ((lane >> 3) & 1)) ^ (lane & 7)) << 4), W4 + 4 * j);
  ldsm4t(sb + S_W4 + 2176 + (lane >> 3) * 32 + (lane & 1) * 16, wx);
  target = (target / NCTA + 1) * NCTA;
  if (tid == 15 * 32) bar_wait(target);
  if (warp == 15) TM(6);
  __syncthreads();
  TM(7);
  const int cnt = sm32[S_VAR / 4];
  uint2 r[RPT]; u32 gx[RPT], gy[RPT], rv[RPT];
#pragma unroll
  for (int k = 0; k < RPT; k++) r[k] = tid + k * NT < cnt ? __ldcg(&g_list[cta * CAP + tid + k * NT]) : make_uint2(0, ~0u);
  const u32 novf = __ldcg(&g_novf);
  auto st_wh = [&]()  {
    int k = tid >> 3, c = tid & 7, sw = ((k >> 3) & 3) * 2 + (k & 1);
    st_perm(sb + S_WH, k, c, sw, w1);
    st_perm(sb + S_WH + 8192, k, c, k & 7, w2);
  };
  if (tid == 14 * 32) asm volatile("red.release.gpu.global.add.u32 [%0],1;" ::"l"(&g_bar2[32]) : "memory");
  const bool last = cnt > (RPT - 1) * NT + warp * 32;
#pragma unroll
  for (int k = 0; k < RPT; k++) {
    if (k < RPT - 1 || last) {
      u32 s = r[k].x & 0xffff;
      u32 x = sm32[(s * 3) >> 1], y = sm32[((s * 3) >> 1) + 1];
      uint2 pd = *(const uint2*)(smem + S_LP + (lane & 15) * 8 + ((r[k].x >> 9) & 0x7f80));
      rv[k] = ~0u;
      if (r[k].y != ~0u) rv[k] = atomicAdd((u32*)(smem + S_GC + prmt(pd.y, 0, 0x4442)), 128u);
      u32 sh = s << 4;
      x = __funnelshift_r(x, y, sh); y = __funnelshift_r(y, 0, sh);
      x = hsub2(pd.x, x); y = hsub2(pd.y, y);
      u32 qx = hmul2(x, x), qy = hmul2(y, y);
      if (k == 3) pf_ea(0, PB);
      if (k == 9) pf_ea(PB, PC);
      gx[k] = x; gy[k] = pack2(blo(y), blo(qx) + bhi(qx) + blo(qy));
      r[k].y = prmt(r[k].y, pd.y, 0x7210);
      r[k].x = s;
    }
  }
  __syncthreads();
  TM(8);
  pf_ea(PC, PD);
  u32 b2 = target;
  if (tid == 14 * 32) asm volatile("ld.relaxed.gpu.global.u32 %0,[%1];" : "=r"(b2) : "l"(&g_bar2[32]) : "memory");
  u32 ua, ub, pv;
  u32 Ac[8], X[8];
  {
    const u32 c = sm32[S_GC / 4 + lane] >> 7, cp = (c + 15) & ~15u;
    u32 d = min((__reduce_max_sync(~0u, cp) - cp) >> 4, 7u), eq = ~0u, lt = 0;
#pragma unroll
    for (int b = 2; b >= 0; b--) {
      u32 m = __ballot_sync(~0u, (d >> b) & 1);
      if ((d >> b) & 1) { lt |= eq & ~m; eq &= m; } else eq &= ~m;
    }
    const int rank = __popc(lt) + __popc(eq & ((1u << lane) - 1)), slot = rank < 16 ? 2 * rank : 63 - 2 * rank;
    sts32(sb + S_GC + 128 + slot * 4, cp);
    __syncwarp();
    u32 x = lds32(sb + S_GC + 128 + lane * 4);
#pragma unroll
    for (int o = 1; o < 32; o <<= 1) { u32 y = __shfl_up_sync(~0u, x, o); if (lane >= o) x += y; }
    x = __shfl_sync(~0u, x, slot);
    const u32 st = x - cp, st4 = st * 4;
#pragma unroll
    for (int k = 0; k < RPT; k++) {
      if (k < RPT - 1 || last) {
        u32 q = __shfl_sync(~0u, st4, rv[k]) + (rv[k] >> 5);
        if (rv[k] != ~0u) { sts32(sb + S_SO + q, r[k].x); sts32(sb + S_ED + q, r[k].y); sts64(sb + S_G + q * 2, gx[k], gy[k]); }
      }
    }
    int gsel = 2 * warp + (lane >> 4);
    u32 q = __shfl_sync(~0u, st + c, gsel) + (lane & 15), qe = __shfl_sync(~0u, x, gsel);
    if (q < qe) { sts32(sb + S_SO + q * 4, cta * 160 + gsel * 5); sts32(sb + S_ED + q * 4, 0x33000000u | (e0 + gsel * 4)); sts64(sb + S_G + q * 8, 0, 0); }
    u32 pk = (st >> 4) | ((x >> 4) << 10) | (lane * (6 << 20));
    ua = __reduce_max_sync(~0u, slot == 2 * warp ? pk : 0); ub = __reduce_max_sync(~0u, slot == 2 * warp + 1 ? pk : 0);
    int la = ua >> 20, lb = ub >> 20;
    int c8 = lane & 7, ra = (c8 & 3) == 3 ? 192 : la + c8 - (c8 >> 2), rb = (c8 & 3) == 3 ? 192 : lb + c8 - (c8 >> 2);
    u32 aa = sb + S_A + ra * 128 + (((lane >> 3) ^ (ra & 7)) << 4), ab = sb + S_A + rb * 128 + (((lane >> 3) ^ (rb & 7)) << 4);
    ldsm4t(aa, Ac); ldsm4t(aa ^ 64, Ac + 4); ldsm4t(ab, X); ldsm4t(ab ^ 64, X + 4);
    pv = lds32(sb + S_LP + min((t & 2 ? lb : la) + g - (g >> 2), NPC - 1) * 128 + lane * 4);
  }
  const u32 stg = sb + S_STG + warp * 2 * STG;
  const int q4 = lane >> 3, c8 = lane & 7;
  const u64 bptr = (u64)g_B | (c8 * 16), eptr = (u64)p.ea | ((lane & 1) * 16);
  u32 cpB0 = stg + q4 * 512 + ((c8 ^ (2 * q4)) << 4), cpB1 = cpB0 ^ 16;
  u32 cpE = stg + 2048 + q4 * 128 + ((4 * (((lane >> 1) ^ q4) & 1) + 2 * ((lane >> 2) & 1) + ((lane ^ (q4 >> 1)) & 1)) << 4);
  u32 ldB[4];
#pragma unroll
  for (int mt = 0; mt < 4; mt++) ldB[mt] = stg + (4 * (c8 >> 1) + 2 * (q4 & 1) + (c8 & 1)) * 128 + (((2 * mt + (q4 >> 1)) ^ c8) << 4);
  u32 ldE = stg + 2048 + (c8 >> 1) * 128 + ((4 * (((lane >> 4) ^ (c8 >> 1)) & 1) + 2 * (c8 & 1) + ((q4 ^ (c8 >> 2)) & 1)) << 4);
  u32 tlo = g < 3 ? 0x3fu << (8 * g) : 0, thi = (g >= 4 && g < 7) ? 0x3fu << (8 * (g - 4)) : 0;
  auto opq = [&](u32& v) { v = __shfl_sync(~0u, v, lane); };
  opq(cpB0); opq(cpB1); opq(cpE); opq(ldE); opq(tlo); opq(thi); opq(ldB[0]); opq(ldB[1]); opq(ldB[2]); opq(ldB[3]);
  const u32 to0 = (ua & 1023) * 64;
  u32 aSO = sb + S_SO + q4 * 16 + to0, aE1 = sb + S_ED + (lane >> 1) * 4 + to0, aE4 = sb + S_ED + t * 16 + to0, aG = sb + S_G + c8 * 16 + 2 * to0;
  auto issue = [&](uint4 so, u32 ed, u32 off, int pr) {
    asm volatile("{.reg .b64 a,b,c,d,e; .reg .pred q; setp.ne.s32 q,%10,0;\n"
      "mad.wide.u32 a,%3,128,%8; mad.wide.u32 b,%4,128,%8; mad.wide.u32 c,%5,128,%8; mad.wide.u32 d,%6,128,%8; mad.wide.u32 e,%7,32,%9;\n"
      "@q cp.async.cg.shared.global [%0],[a],16; @q cp.async.cg.shared.global [%1+128],[b],16;\n"
      "@q cp.async.cg.shared.global [%0+256],[c],16; @q cp.async.cg.shared.global [%1+384],[d],16;\n"
      "@q cp.async.cg.shared.global [%2],[e],16; cp.async.commit_group;}"
      ::"r"(cpB0 + off), "r"(cpB1 + off), "r"(cpE + off), "r"(so.x), "r"(so.y), "r"(so.z), "r"(so.w), "r"(ed & 0xffffffu), "l"(bptr), "l"(eptr),
        "r"(pr) : "memory");
  };
  int n = (ub & 1023) - (ua & 1023), c3 = 3 + (ub & 1023) - ((ub >> 10) & 1023);
  if ((int)(b2 - target) < 0) bar_wait(target, &g_bar2[32]);
  if (novf) overflow_path(p, novf);
  __syncthreads();
  TM(9);
#pragma unroll
  for (int k = 0; k < 2; k++) issue(lds128(aSO + k * 64), lds32(aE1 + k * 64), k * STG, n + 3 - c3 > k);
    sts128(sb + S_X + warp * 1024 + lane * 16, make_uint4(X[0], X[1], X[2], X[3]));
    sts128(sb + S_X + warp * 1024 + 512 + lane * 16, make_uint4(X[4], X[5], X[6], X[7]));
  sts32(sb + S_ST + tid * 4, pv);
  if (lane == 0) sts128(sb + S_ST + 2048 + warp * 16, make_uint4(ua >> 20, novf, ub >> 20, 0));
  __syncwarp();
  {
    st_wh();
    __syncwarp();
    if (lane == 0) asm volatile("mbarrier.arrive.shared.b64 _,[%0];" ::"r"(sb + S_VAR + 8) : "memory");
  }
  u32 Sx[3], Sy[3] = {0, 0, 0}, ta, tb;
  auto build = [&](uint4 ed, u32& na, u32& nb, u32 vN) {
    na = prmt(tlo, thi, prmt(ed.x, ed.z, 0x73)); nb = prmt(tlo, thi, prmt(ed.y, ed.w, 0x73));
    na = g == 3 ? vN : na; nb = g == 7 ? vN : nb;
    ta = movm(na); tb = movm(nb);
  };
  Sx[2] = ldsm1t(aG);
  build(lds128(aE4), Sx[0], Sx[1], Sx[2]);
  float seg[4][4], pa[4];
  int gi = 0;
  auto reset = [&]() {
#pragma unroll
    for (int j = 0; j < 4; j++) { seg[j][0] = seg[j][1] = seg[j][2] = seg[j][3] = 0.f; pa[j] = 0.f; }
  };
  float x[4][4], y[4][4];
  u32 ca, cb;
  auto back = [&](int mt, u32 s0, u32 s1) {
    u32 m2 = pack2(silu_h(y[mt][0]), silu_h(y[mt][1])), m3 = pack2(silu_h(y[mt][2]), silu_h(y[mt][3]));
    u32 m0 = pack2(silu_h(x[mt][0]), silu_h(x[mt][1])), m1 = pack2(silu_h(x[mt][2]), silu_h(x[mt][3]));
    mma16(seg[mt], m0, m1, m2, m3, s0, s1);
    ca = hfma2l(m0, wx[mt], mt ? ca : 0x80008000u); cb = hfma2l(m2, wx[mt], mt ? cb : 0x80008000u);
    ca = hfma2h(m1, wx[mt], ca); cb = hfma2h(m3, wx[mt], cb);
  };
  auto body = [&](const u32 off, const u32 to, const u32* C, u32* O) {
    asm volatile("cp.async.wait_group 1;" ::: "memory");
    __syncwarp();
    u32 ef[4], b[4][4];
    auto front = [&](int mt) {
#pragma unroll
      for (int i = 0; i < 4; i++) { x[mt][i] = __uint_as_float(b[mt][i] * 65536u + 0x8000u); y[mt][i] = __uint_as_float(b[mt][i]); }
      mma16(y[mt], W4[4 * mt], W4[4 * mt + 1], W4[4 * mt + 2], W4[4 * mt + 3], ef[2], ef[3]);
      mma16(x[mt], W4[4 * mt], W4[4 * mt + 1], W4[4 * mt + 2], W4[4 * mt + 3], ef[0], ef[1]);
      mma8(y[mt], Ac[2 * mt], Ac[2 * mt + 1], tb);
      mma8(x[mt], Ac[2 * mt], Ac[2 * mt + 1], ta);
    };
    ldsm4(ldE + off, ef);
    ldsm4t(ldB[0] + off, b[0]);
    ldsm4t(ldB[1] + off, b[1]);
    uint4 so = lds128(aSO + to + 128);
    u32 e1 = lds32(aE1 + to + 128);
    back(3, O[0], O[1]);
    u32 keep = g < 4 ? ca : cb, send = g < 4 ? cb : ca;
    front(0);
    { ldsm4t(ldB[2] + off, b[2]); ldsm4t(ldB[3] + off, b[3]); }
    front(1);
    issue(so, e1, off, to ? n > c3 : n >= c3);
    keep = hadd2(keep, __shfl_xor_sync(~0u, send, 16));
    back(0, C[0], C[1]);
    keep = hadd2(keep, __shfl_xor_sync(~0u, keep, 8));
    front(2);
    keep = hadd2(keep, __shfl_xor_sync(~0u, keep, 4));
    back(1, C[0], C[1]);
    mma8(pa, O[0], O[1], hmul2(keep, O[2]));
    front(3);
    uint4 ed = lds128(aE4 + to + 64);
    O[2] = ldsm1t(aG + 2 * to + 128);
    build(ed, O[0], O[1], O[2]);
    back(2, C[0], C[1]);
  };
  auto fin = [&]() {
    uint4 gv = lds128(sb + S_ST + 2048 + warp * 16);
    gi = gv.w;
    n0 = node_of(gv.x, g, cta); n1 = node_of(gv.z, g, cta);
    load_h(p, gi ? n0 : -1, gi ? n1 : -1, t, h0, h1);
    back(3, n ? Sx[0] : Sy[0], n ? Sx[1] : Sy[1]);
    u32 keep = g < 4 ? ca : cb, send = g < 4 ? cb : ca;
    keep = hadd2(keep, __shfl_xor_sync(~0u, send, 16));
    keep = hadd2(keep, __shfl_xor_sync(~0u, keep, 8));
    keep = hadd2(keep, __shfl_xor_sync(~0u, keep, 4));
    mma8(pa, n ? Sx[0] : Sy[0], n ? Sx[1] : Sy[1], hmul2(keep, n ? Sx[2] : Sy[2]));
#pragma unroll
    for (int j = 0; j < 3; j++) { if (n) Sx[j] = 0; else Sy[j] = 0; }
    __syncwarp();
    sts32(sb + S_ST + 2048 + warp * 16 + 12, 1);
    const u32 pv = lds32(sb + S_ST + (tid ^ (2 * gi)) * 4);
    const int nd = gi ? n1 : n0;
    if (gv.y) {
      int na = __shfl_sync(~0u, nd, 8 * t), nb = __shfl_sync(~0u, nd, 8 * t + 4);
#pragma unroll
      for (int mt = 0; mt < 4; mt++) {
        if (na >= 0) { seg[mt][0] += 0.5f * __ldcg(&g_acc[na * 68 + 16 * mt + g]); seg[mt][2] += 0.5f * __ldcg(&g_acc[na * 68 + 16 * mt + 8 + g]); }
        if (nb >= 0) { seg[mt][1] += 0.5f * __ldcg(&g_acc[nb * 68 + 16 * mt + g]); seg[mt][3] += 0.5f * __ldcg(&g_acc[nb * 68 + 16 * mt + 8 + g]); }
      }
      if (nd >= 0 && t < 2) { pa[0] += 0.5f * __ldcg(&g_acc[nd * 68 + 64 + 2 * t]); pa[1] += 0.5f * __ldcg(&g_acc[nd * 68 + 65 + 2 * t]); }
    }
    float u0 = pa[0] + __shfl_xor_sync(~0u, pa[2], 2), u1 = pa[1] + __shfl_xor_sync(~0u, pa[3], 2);
    if (nd >= 0 && t < 2) {
      u32 o = hadd2(pv, pack2(2.f * u0, 2.f * u1));
      unsigned short* po = (unsigned short*)p.out + NN * 64 + nd * 3 + 2 * t;
      po[0] = o & 0xffff;
      if (t == 0) po[1] = o >> 16;
    }
    {
      const u32 xa = sb + S_X + warp * 1024 + lane * 16;
      uint4 x0 = lds128(xa), x1 = lds128(xa + 512);
      Ac[0] = x0.x; Ac[1] = x0.y; Ac[2] = x0.z; Ac[3] = x0.w; Ac[4] = x1.x; Ac[5] = x1.y; Ac[6] = x1.z; Ac[7] = x1.w;
      u32 X[8];
#pragma unroll
      for (int mt = 0; mt < 4; mt++) {
        X[2 * mt] = movm(pack2(2.f * seg[mt][0], 2.f * seg[mt][1]));
        X[2 * mt + 1] = movm(pack2(2.f * seg[mt][2], 2.f * seg[mt][3]));
      }
      sts128(xa, make_uint4(X[0], X[1], X[2], X[3])); sts128(xa + 512, make_uint4(X[4], X[5], X[6], X[7]));
    }
  };
  n *= 2;
#pragma unroll 1
  do {
    reset();
    ca = cb = 0;
#pragma unroll
    for (int j = 0; j < 4; j++) x[3][j] = y[3][j] = 0.f;
    n = __reduce_max_sync(~0u, n);
    const bool odd = n & 1;
    n >>= 1;
    if (n > (int)odd) {
      if (odd) { body(STG, 64, Sy, Sx); aSO += 128; aE1 += 128; aE4 += 128; aG += 256; n -= 2; }
      while (n) {
        body(0, 0, Sx, Sy);
        if (n == 1) break;
        body(STG, 64, Sy, Sx);
        aSO += 128; aE1 += 128; aE4 += 128; aG += 256; n -= 2;
      }
    }
    fin();
    n = 3 * n + 6 - 2 * c3; c3 = 3;
  } while (!gi);
  TM(10);
  {
    u32 done, it = 0;
    do {
      asm volatile("{.reg .pred q; mbarrier.try_wait.parity.shared.b64 q,[%1],0; selp.u32 %0,1,0,q;}" : "=r"(done) : "r"(sb + S_VAR + 8) : "memory");
      if (++it > (1u << 24)) __trap();
    } while (!done);
  }
  {
    u32 X[8];
    *(uint4*)X = lds128(sb + S_X + warp * 1024 + lane * 16); *(uint4*)(X + 4) = lds128(sb + S_X + warp * 1024 + 512 + lane * 16);
    float acc[8][4];
#pragma unroll
    for (int j = 0; j < 8; j++) acc[j][0] = acc[j][1] = acc[j][2] = acc[j][3] = 0.f;
#pragma unroll
    for (int s = 0; s < 4; s++) {
      u32 row = sb + S_WH + 8192 + (16 * s + (lane & 15)) * 128;
#pragma unroll
      for (int j = 0; j < 8; j += 2) {
        u32 w[4]; ldsm4t(row + (((j + (lane >> 4)) ^ c8) << 4), w);
        mma16(acc[j], Ac[2 * s], X[2 * s], Ac[2 * s + 1], X[2 * s + 1], w[0], w[1]);
        mma16(acc[j + 1], Ac[2 * s], X[2 * s], Ac[2 * s + 1], X[2 * s + 1], w[2], w[3]);
      }
    }
    gemm_perm(acc, h0, h1, sb + S_WH, lane);
    u32* a = (u32*)h0; u32* c = (u32*)h1;
#pragma unroll
    for (int j = 0; j < 8; j++) {
      a[j] = hadd2(a[j], pack2(silu_h(0.5f * acc[j][0]), silu_h(0.5f * acc[j][1])));
      c[j] = hadd2(c[j], pack2(silu_h(0.5f * acc[j][2]), silu_h(0.5f * acc[j][3])));
    }
    uint4* o = (uint4*)p.out;
    if (n0 >= 0) { o[n0 * 8 + t] = h0[0]; o[n0 * 8 + t + 4] = h0[1]; }
    if (n1 >= 0) { o[n1 * 8 + t] = h1[0]; o[n1 * 8 + t + 4] = h1[1]; }
  }
  TM(11);
}

__global__ void fb_zero() { for (int i = blockIdx.x * blockDim.x + threadIdx.x; i < NN * 68; i += gridDim.x * blockDim.x) g_acc[i] = 0.f; }
__global__ void fb_edge(const __grid_constant__ P p) { for (int e = blockIdx.x * 8 + (threadIdx.x >> 5); e < NE; e += gridDim.x * 8) slow_edge(p, e, threadIdx.x & 31); }
__global__ void fb_node(const P p) {
  int n = blockIdx.x, f = threadIdx.x;
  float x = 0.f;
  for (int k = 0; k < 64; k++) x += b2f(p.h[n * 64 + k]) * b2f(p.wh[k * 64 + f]) + rbf(g_acc[n * 68 + k]) * b2f(p.wh[(64 + k) * 64 + f]);
  p.out[n * 64 + f] = __float2bfloat16_rn(b2f(p.h[n * 64 + f]) + rbf(silu_h(0.5f * x)));
  if (f < 3) p.out[NN * 64 + n * 3 + f] = __float2bfloat16_rn(b2f(p.pos[n * 3 + f]) + rbf(g_acc[n * 68 + 64 + f]));
}

extern "C" void kernel_launch(void* const* d_in, const int* in_sizes, int n_in, void* d_out, int out_size) {
  static int mode = -1;
  if (mode < 0) {
    int dev = 0, sms = 0, occ = 0;
    cudaGetDevice(&dev);
    cudaDeviceGetAttribute(&sms, cudaDevAttrMultiProcessorCount, dev);
    cudaError_t e = cudaFuncSetAttribute(egnn_kernel, cudaFuncAttributeMaxDynamicSharedMemorySize, S_END);
    if (e == cudaSuccess) e = cudaOccupancyMaxActiveBlocksPerMultiprocessor(&occ, egnn_kernel, NT, S_END);
    mode = (e == cudaSuccess && occ * sms >= NCTA) ? 1 : 0;
    cudaGetLastError();
  }
  P p;
  p.h = (const __nv_bfloat16*)d_in[0]; p.pos = (const __nv_bfloat16*)d_in[1]; p.ea = (const __nv_bfloat16*)d_in[2];
  p.src = (const int*)d_in[3]; p.dst = (const int*)d_in[4];
  p.we = (const __nv_bfloat16*)d_in[5]; p.wx = (const __nv_bfloat16*)d_in[6]; p.wh = (const __nv_bfloat16*)d_in[7];
  p.out = (__nv_bfloat16*)d_out;
  size_t al = (size_t)d_out;
  for (int i = 0; i < 8; i++) al |= (size_t)d_in[i];
  if (mode == 1 && (al & 31) == 0) {
    egnn_kernel<<<NCTA, NT, S_END>>>(p);
  } else {
    fb_zero<<<512, 256>>>(); fb_edge<<<2048, 256>>>(p); fb_node<<<NN, 64>>>(p);
  }
}
```

```cpp
#include <cuda_runtime.h>
#include <cuda_bf16.h>
#include <stdint.h>

#pragma nv_diag_suppress 549
typedef unsigned int u32;
typedef unsigned long long u64;
#define DEVI __device__ __forceinline__

constexpr int NN = 25000, NE = 800000;
constexpr int NCTA = 132, NT = 512, NPC = 190, CHUNK = 6064, CAP = 6656, MAXPOS = 7136;
constexpr int RPT = 13;
constexpr int S_POS = 0, S_REC = 150016, S_A = S_REC, S_LP = S_A + 193 * 128;
constexpr int S_CNT = S_REC + (CHUNK + 3 * NCTA) * 8, S_DEL = S_CNT + 528, S_GB = S_DEL + 528, S_MB = S_GB + 528, S_GC = 199056, S_VAR = S_GC + 256;
constexpr int S_X = 199680, S_WH = S_X + 16384, S_W1 = S_WH, S_W2 = S_W1 + 8192, S_END = S_WH + 16384, S_W4 = S_X + 5120;
constexpr int S_SO = 0, S_ED = MAXPOS * 4, S_G = MAXPOS * 8, S_STG = MAXPOS * 16, STG = 2560, S_ST = S_STG + 32 * STG;
static_assert(S_LP + NPC * 128 <= S_GC && S_VAR + 16 <= S_X && S_MB + 8 <= S_W4 && S_ST + 2048 + 256 <= S_GC && S_END <= 232448, "smem");

__device__ __align__(128) uint2 g_list[NCTA * CAP];
__device__ __align__(128) uint4 g_B[NN * 8];
__device__ u32 g_cnt[NCTA * 8];
__device__ u32 g_bar, g_novf, g_bar2[64];
__device__ u32 g_ovf[NE];
__device__ float g_acc[NN * 68];

DEVI u32 lds32(u32 a) { u32 v; asm volatile("ld.shared.u32 %0,[%1];" : "=r"(v) : "r"(a)); return v; }
DEVI uint2 lds64(u32 a) { uint2 v; asm volatile("ld.shared.v2.u32 {%0,%1},[%2];" : "=r"(v.x), "=r"(v.y) : "r"(a)); return v; }
DEVI uint4 lds128(u32 a) { uint4 v; asm volatile("ld.shared.v4.u32 {%0,%1,%2,%3},[%4];" : "=r"(v.x), "=r"(v.y), "=r"(v.z), "=r"(v.w) : "r"(a)); return v; }
DEVI void sts32(u32 a, u32 v) { asm volatile("st.shared.u32 [%0],%1;" ::"r"(a), "r"(v) : "memory"); }
DEVI void sts64(u32 a, u32 x, u32 y) { asm volatile("st.shared.v2.u32 [%0],{%1,%2};" ::"r"(a), "r"(x), "r"(y) : "memory"); }
DEVI void sts128(u32 a, uint4 v) { asm volatile("st.shared.v4.u32 [%0],{%1,%2,%3,%4};" ::"r"(a), "r"(v.x), "r"(v.y), "r"(v.z), "r"(v.w) : "memory"); }
DEVI u32 atoms_inc(u32 a) { u32 v; asm volatile("atom.shared.add.u32 %0,[%1],1;" : "=r"(v) : "r"(a) : "memory"); return v; }
DEVI void ldsm4(u32 a, u32* r) { asm volatile("ldmatrix.sync.aligned.m8n8.x4.shared.b16 {%0,%1,%2,%3},[%4];" : "=r"(r[0]), "=r"(r[1]), "=r"(r[2]), "=r"(r[3]) : "r"(a)); }
DEVI void ldsm4t(u32 a, u32* r) { asm volatile("ldmatrix.sync.aligned.m8n8.x4.trans.shared.b16 {%0,%1,%2,%3},[%4];" : "=r"(r[0]), "=r"(r[1]), "=r"(r[2]), "=r"(r[3]) : "r"(a)); }
DEVI u32 ldsm1t(u32 a) { u32 r; asm volatile("ldmatrix.sync.aligned.m8n8.x1.trans.shared.b16 {%0},[%1];" : "=r"(r) : "r"(a)); return r; }
DEVI u32 movm(u32 a) { u32 r; asm("movmatrix.sync.aligned.m8n8.trans.b16 %0,%1;" : "=r"(r) : "r"(a)); return r; }
DEVI void mma16(float* c, u32 a0, u32 a1, u32 a2, u32 a3, u32 b0, u32 b1) {
  asm("mma.sync.aligned.m16n8k16.row.col.f32.bf16.bf16.f32 {%0,%1,%2,%3},{%4,%5,%6,%7},{%8,%9},{%0,%1,%2,%3};"
      : "+f"(c[0]), "+f"(c[1]), "+f"(c[2]), "+f"(c[3]) : "r"(a0), "r"(a1), "r"(a2), "r"(a3), "r"(b0), "r"(b1));
}
DEVI void mma8(float* c, u32 a0, u32 a1, u32 b0) {
  asm("mma.sync.aligned.m16n8k8.row.col.f32.bf16.bf16.f32 {%0,%1,%2,%3},{%4,%5},{%6},{%0,%1,%2,%3};"
      : "+f"(c[0]), "+f"(c[1]), "+f"(c[2]), "+f"(c[3]) : "r"(a0), "r"(a1), "r"(b0));
}
DEVI u32 pack2(float lo, float hi) { u32 r; asm("cvt.rn.bf16x2.f32 %0,%1,%2;" : "=r"(r) : "f"(hi), "f"(lo)); return r; }
DEVI u32 pack2z(float lo, float hi) { u32 r; asm("cvt.rz.bf16x2.f32 %0,%1,%2;" : "=r"(r) : "f"(hi), "f"(lo)); return r; }
DEVI u32 hfma2l(u32 a, u32 b, u32 c) { u32 r; asm("{.reg .b16 l,h; .reg .b32 d; mov.b32 {l,h},%2; mov.b32 d,{l,l}; fma.rn.bf16x2 %0,%1,d,%3;}" : "=r"(r) : "r"(a), "r"(b), "r"(c)); return r; }
DEVI u32 hfma2h(u32 a, u32 b, u32 c) { u32 r; asm("{.reg .b16 l,h; .reg .b32 d; mov.b32 {l,h},%2; mov.b32 d,{h,h}; fma.rn.bf16x2 %0,%1,d,%3;}" : "=r"(r) : "r"(a), "r"(b), "r"(c)); return r; }
DEVI int node_of(int l0, int g, int cta) { int l = l0 + g - (g >> 2), n = cta * NPC + l; return ((g & 3) == 3 || l >= NPC || n >= NN) ? -1 : n; }
DEVI u32 hmul2(u32 a, u32 b) { u32 r; asm("mul.rn.bf16x2 %0,%1,%2;" : "=r"(r) : "r"(a), "r"(b)); return r; }
DEVI u32 hadd2(u32 a, u32 b) { u32 r; asm("add.rn.bf16x2 %0,%1,%2;" : "=r"(r) : "r"(a), "r"(b)); return r; }
DEVI u32 hsub2(u32 a, u32 b) { u32 r; asm("sub.rn.bf16x2 %0,%1,%2;" : "=r"(r) : "r"(a), "r"(b)); return r; }
DEVI u32 hfma2(u32 a, u32 b, u32 c) { u32 r; asm("fma.rn.bf16x2 %0,%1,%2,%3;" : "=r"(r) : "r"(a), "r"(b), "r"(c)); return r; }
DEVI u32 prmt(u32 a, u32 b, u32 c) { u32 r; asm("prmt.b32 %0,%1,%2,%3;" : "=r"(r) : "r"(a), "r"(b), "r"(c)); return r; }
DEVI float blo(u32 v) { return __uint_as_float(v << 16); }
DEVI float bhi(u32 v) { return __uint_as_float(v & 0xffff0000u); }
DEVI float silu_h(float hx) { float t; asm("tanh.approx.f32 %0,%1;" : "=f"(t) : "f"(hx)); return fmaf(hx, t, hx); }
DEVI void cp16(u32 s, const void* g) { asm volatile("cp.async.cg.shared.global [%0],[%1],16;" ::"r"(s), "l"(g) : "memory"); }
DEVI const void* madw(u32 a, u32 b, const void* c) { const void* r; asm("mad.wide.u32 %0,%1,%2,%3;" : "=l"(r) : "r"(a), "r"(b), "l"(c)); return r; }
DEVI u32 ld_acq(const u32* p) { u32 v; asm volatile("ld.acquire.gpu.global.u32 %0,[%1];" : "=r"(v) : "l"(p) : "memory"); return v; }
DEVI float b2f(__nv_bfloat16 x) { return __bfloat162float(x); }
DEVI float rbf(float x) { return __bfloat162float(__float2bfloat16_rn(x)); }

DEVI u32 bar_arrive() {
  __threadfence();
  u32 t = atomicAdd(&g_bar, 1u);
  return (t / NCTA + 1) * NCTA;
}
DEVI void bar_wait(u32 target, const u32* bar = &g_bar) {
  u32 it = 0;
  while ((int)(ld_acq(bar) - target) < 0) { if (++it > (1u << 26)) __trap(); }
}
DEVI void grid_sync() {
  __syncthreads();
  if (threadIdx.x == 0) bar_wait(bar_arrive());
  __syncthreads();
}

struct P {
  const __nv_bfloat16 *h, *pos, *ea; const int *src, *dst; const __nv_bfloat16 *we, *wx, *wh; __nv_bfloat16* out;
};

__device__ __noinline__ void slow_edge(const P& p, int e, int lane) {
  int s = p.src[e], d = p.dst[e];
  float df[3], d2 = 0.f;
  for (int c = 0; c < 3; c++) { df[c] = rbf(b2f(p.pos[d * 3 + c]) - b2f(p.pos[s * 3 + c])); d2 += rbf(df[c] * df[c]); }
  d2 = rbf(d2);
  const u32* w = (const u32*)p.we + lane;
  float x0 = d2 * blo(w[128 * 32]), x1 = d2 * bhi(w[128 * 32]);
  for (int k = 0; k < 64; k++) {
    float a = b2f(p.h[d * 64 + k]), b = b2f(p.h[s * 64 + k]);
    u32 wa = w[k * 32], wb = w[(64 + k) * 32];
    x0 += a * blo(wa) + b * blo(wb); x1 += a * bhi(wa) + b * bhi(wb);
  }
  for (int k = 0; k < 16; k++) { float a = b2f(p.ea[(size_t)e * 16 + k]); u32 wa = w[(129 + k) * 32]; x0 += a * blo(wa); x1 += a * bhi(wa); }
  float m0 = rbf(silu_h(0.5f * x0)), m1 = rbf(silu_h(0.5f * x1));
  float cs = m0 * b2f(p.wx[2 * lane]) + m1 * b2f(p.wx[2 * lane + 1]);
  for (int o = 16; o; o >>= 1) cs += __shfl_xor_sync(~0u, cs, o);
  cs = rbf(cs);
  atomicAdd(&g_acc[d * 68 + 2 * lane], m0); atomicAdd(&g_acc[d * 68 + 2 * lane + 1], m1);
  if (lane < 3) atomicAdd(&g_acc[d * 68 + 64 + lane], rbf((lane == 0 ? df[0] : lane == 1 ? df[1] : df[2]) * cs));
}

__device__ __noinline__ void overflow_path(const P& p, u32 novf) {
  for (int i = blockIdx.x * NT + threadIdx.x; i < NN * 68; i += NCTA * NT) g_acc[i] = 0.f;
  grid_sync();
  if (blockIdx.x == 0 && threadIdx.x == 0) g_novf = 0;
  for (u32 i = blockIdx.x * 16 + (threadIdx.x >> 5); i < novf; i += NCTA * 16) slow_edge(p, __ldcg(&g_ovf[i]), threadIdx.x & 31);
  grid_sync();
}

DEVI void gemm_perm(float (*acc)[4], const uint4* h0, const uint4* h1, u32 wbase, int lane) {
  const int r = lane & 7, b = (lane >> 3) & 1, jo = lane >> 4;
  const u32* a = (const u32*)h0; const u32* c = (const u32*)h1;
#pragma unroll
  for (int s = 0; s < 4; s++) {
    u32 row = wbase + (32 * (s >> 1) + 8 * (r >> 1) + 4 * (s & 1) + 2 * b + (r & 1)) * 128;
#pragma unroll
    for (int j = 0; j < 8; j += 2) {
      u32 w[4]; ldsm4t(row + (((j + jo) ^ r) << 4), w);
      mma16(acc[j], a[2 * s], c[2 * s], a[2 * s + 1], c[2 * s + 1], w[0], w[1]);
      mma16(acc[j + 1], a[2 * s], c[2 * s], a[2 * s + 1], c[2 * s + 1], w[2], w[3]);
    }
  }
}
DEVI void load_h(const P& p, int n0, int n1, int t, uint4* h0, uint4* h1) {
  const uint4 z = make_uint4(0, 0, 0, 0);
  const uint4* hp = (const uint4*)p.h;
  h0[0] = n0 >= 0 ? __ldg(hp + n0 * 8 + t) : z; h0[1] = n0 >= 0 ? __ldg(hp + n0 * 8 + t + 4) : z;
  h1[0] = n1 >= 0 ? __ldg(hp + n1 * 8 + t) : z; h1[1] = n1 >= 0 ? __ldg(hp + n1 * 8 + t + 4) : z;
}
DEVI void st_perm(u32 base, int k, int c, int sw, uint4 v) {
  u32 a = base + k * 128 + (c & 3) * 4; int j = c & 4;
  sts32(a + (((j) ^ sw) << 4), v.x); sts32(a + (((j + 1) ^ sw) << 4), v.y);
  sts32(a + (((j + 2) ^ sw) << 4), v.z); sts32(a + (((j + 3) ^ sw) << 4), v.w);
}

constexpr int NG = 4;
constexpr int PB = 2, PC = 5, PD = 11;
#define HV 2
#define TM(i)

__global__ void __launch_bounds__(NT, 1) egnn_kernel(const __grid_constant__ P p) {
  extern __shared__ __align__(128) unsigned char smem[];
  const u32 sb = (u32)__cvta_generic_to_shared(smem);
  const int tid = threadIdx.x, lane = tid & 31, warp = tid >> 5, cta = blockIdx.x;
  const int g = lane >> 2, t = lane & 3;
  TM(0);
  u32* const sm32 = (u32*)smem;
  auto pos_tma = [&](int k0, int k1) {
    if (tid == 64) {
      for (int k = k0; k < k1; k++) {
        int kk = (k + cta) % 5;
        asm volatile("cp.async.bulk.shared::cluster.global.mbarrier::complete_tx::bytes [%0],[%1],%2,[%3];"
                     ::"r"(sb + S_POS + kk * 30000), "l"((const char*)p.pos + kk * 30000), "r"(30000), "r"(sb + S_MB) : "memory");
      }
    }
  };
  if (tid == 64) {
    asm volatile("mbarrier.init.shared.b64 [%0],1;" ::"r"(sb + S_MB) : "memory");
    asm volatile("fence.mbarrier_init.release.cluster;" ::: "memory");
    asm volatile("mbarrier.arrive.expect_tx.shared.b64 _,[%0],%1;" ::"r"(sb + S_MB), "r"(NN * 6) : "memory");
  }
  pos_tma(0, 5);
  const int e0 = cta * CHUNK, ne4 = (min(NE, e0 + CHUNK) - e0) >> 2;
  const bool v3 = tid + 2 * NT < ne4;
  int4 dv[3], sv[3];
#pragma unroll
  for (int k = 0; k < 3; k++) if (k < 2 || v3) dv[k] = __ldcs((const int4*)(p.dst + e0) + tid + k * NT);
#pragma unroll
  for (int k = 0; k < 3; k++) if (k < 2 || v3) sv[k] = __ldcs((const int4*)(p.src + e0) + tid + k * NT);
  u32 target = 0;
  if (tid < NCTA) sm32[S_CNT / 4 + tid] = 0;
  if (tid >= 14 * 32 && lane == 0) target = __ldcg(warp == 15 ? &g_bar : &g_bar2[32]);
  uint4 h0[2], h1[2];
  int n0, n1;
  {
    int l0 = warp * 16 + g;
    n0 = cta * NPC + l0; n1 = n0 + 8;
    if (l0 >= NPC || n0 >= NN) n0 = -1;
    if (l0 + 8 >= NPC || n1 >= NN) n1 = -1;
  }
  if (tid >= 239) {
    asm volatile("prefetch.global.L2 [%0];" ::"l"(tid >= 384 ? (const char*)p.wh + (tid - 384) * 128 : (const char*)p.we + (tid - 239) * 128));
  }
  __syncthreads();
  TM(1);
  if (tid == 96) asm volatile("cp.async.bulk.prefetch.L2.global [%0],%1;" ::"l"(p.h + cta * NPC * 64), "r"(min(NPC, NN - cta * NPC) * 128) : "memory");
  u32 rec[12], rk[12];
#pragma unroll
  for (int k = 0; k < 12; k++) {
    if (k < 8 || v3) {
      u32 d = ((const int*)dv)[k], o = __umulhi(d, 22605092u);
      rk[k] = atomicAdd(sm32 + S_CNT / 4 + o, 8u);
      rec[k] = (d + o * (256 - NPC)) << 16;
    }
  }
  uint4 w1 = __ldg((const uint4*)p.we + tid), w2 = __ldg((const uint4*)p.we + 512 + tid);
  if (warp >= 12) h0[0] = __ldg((const uint4*)p.we + 129 * 8 + (tid - 384));
  if (warp == 12 && lane < 16) h0[1] = __ldg(lane < 8 ? (const uint4*)p.we + 128 * 8 + lane : (const uint4*)p.wx + (lane - 8));
  __syncthreads();
  TM(2);
  u32 gb[2], of[2], cn[2] = {0, 0};
  if (warp >= 13) {
    const int j = tid - 13 * 32;
    if (j < NCTA / 2) { uint2 c = lds64(sb + S_CNT + j * 8); cn[0] = c.x; cn[1] = c.y; }
    const u32 c0 = (cn[0] + 31) & ~31u, c1 = (cn[1] + 31) & ~31u;
    if (j < NCTA / 2) { gb[0] = atomicAdd(&g_cnt[j * 16], (c0 >> 3) + (1u << 24)); gb[1] = atomicAdd(&g_cnt[j * 16 + 8], (c1 >> 3) + (1u << 24)); }
    u32 pre = 0;
#pragma unroll
    for (int k = 0; k < 2; k++) if (k < warp - 13) { uint2 v = lds64(sb + S_CNT + (k * 32 + lane) * 8); pre += ((v.x + 31) & ~31u) + ((v.y + 31) & ~31u); }
    pre = __reduce_add_sync(~0u, pre);
    u32 x = c0 + c1;
#pragma unroll
    for (int o = 1; o < 32; o <<= 1) { u32 y = __shfl_up_sync(~0u, x, o); if (lane >= o) x += y; }
    of[1] = pre + x - c1; of[0] = of[1] - c0;
    if (j < NCTA / 2) sts64(sb + S_DEL + j * 8, of[0], of[1]);
#pragma unroll
    for (int k = 0; k < 2; k++) for (u32 i = cn[k]; i & 31; i += 8) sts64(sb + S_REC + of[k] + i, 0, ~0u);
  }
  __syncthreads();
  TM(3);
#pragma unroll
  for (int k = 0; k < 12; k++) if (k < 8 || v3) rk[k] += sm32[S_DEL / 4 + (rec[k] >> 24)];
#pragma unroll
  for (int k = 0; k < 12; k++) if (k < 8 || v3) sts64(sb + S_REC + rk[k], rec[k] | ((const int*)sv)[k], e0 + (tid + (k >> 2) * NT) * 4 + (k & 3));
  {
    int k = tid >> 3, c = tid & 7, sw = ((k >> 3) & 3) * 2 + (k & 1);
    sts128(sb + S_W1 + k * 128 + ((c ^ sw) << 4), w1);
    st_perm(sb + S_W2, k, c, sw, w2);
    const u32 hf = 0x3f003f00u;
    if (warp >= 12) sts128(sb + S_W4 + (k - 48) * 128 + ((c ^ (k & 7)) << 4), make_uint4(hmul2(h0[0].x, hf), hmul2(h0[0].y, hf), hmul2(h0[0].z, hf), hmul2(h0[0].w, hf)));
    if (warp == 12 && lane < 16) sts128(sb + S_W4 + 2048 + lane * 16, h0[1]);
  }
  load_h(p, n0, n1, t, h0, h1);
  if (warp >= 13 && tid - 13 * 32 < NCTA / 2) sts64(sb + S_GB + (tid - 13 * 32) * 8, gb[0], gb[1]);
  asm volatile("fence.proxy.async.shared::cta;" ::: "memory");
  __syncthreads();
  TM(4);
  auto pf_ea = [&](int w0, int w1) {
    if (lane == 0 && warp >= w0 && warp < w1) {
      int nb = 2 * min(CHUNK, NE - e0);
      asm volatile("cp.async.bulk.prefetch.L2.global [%0],%1;" ::"l"((const char*)p.ea + (size_t)e0 * 32 + warp * nb), "r"(nb) : "memory");
    }
  };
  if (lane < (warp < 12 ? NG : (132 - 12 * NG) / 4)) {
    const u32 o = lane + (warp < 12 ? warp * NG : 12 * NG + (warp - 12) * ((132 - 12 * NG) / 4)), c = sm32[S_CNT / 4 + o], src = sb + S_REC + sm32[S_DEL / 4 + o];
    const u32 base = min((sm32[S_GB / 4 + o] & 0xffffffu) * 8, CAP * 8u), fit = min((c + 31) & ~31u, CAP * 8 - base);
    if (fit) asm volatile("cp.async.bulk.global.shared::cta.bulk_group [%0],[%1],%2; cp.async.bulk.commit_group;"
                          ::"l"((char*)g_list + o * (CAP * 8) + base), "r"(src), "r"(fit) : "memory");
    if (fit < c) {
      u32 q = atomicAdd(&g_novf, (c - fit) >> 3);
      for (u32 i = fit; i < c; i += 8) g_ovf[q++] = lds32(src + i + 4);
      __threadfence();
    }
  }
  u32 W4[16], wx[4], o0[8], o1[8];
  w1 = __ldg((const uint4*)p.wh + tid); w2 = __ldg((const uint4*)p.wh + 512 + tid);
  if (warp < 12) {
    float acc[8][4];
#pragma unroll
    for (int j = 0; j < 8; j++) acc[j][0] = acc[j][1] = acc[j][2] = acc[j][3] = 0.f;
    gemm_perm(acc, h0, h1, sb + S_W2, lane);
#pragma unroll
    for (int j = 0; j < 8; j++) { o0[j] = pack2z(0.5f * acc[j][0], 0.5f * acc[j][1]); o1[j] = pack2z(0.5f * acc[j][2], 0.5f * acc[j][3]); }
  }
  asm volatile("cp.async.bulk.wait_group 0; fence.proxy.async.global;" ::: "memory");
  __syncthreads();
  TM(5);
  if (tid == 15 * 32) asm volatile("red.relaxed.gpu.global.add.u32 [%0],1;" ::"l"(&g_bar) : "memory");
  if (warp < 12) {
    if (n0 >= 0) { g_B[n0 * 8 + t] = make_uint4(o0[0], o0[1], o0[2], o0[3]); g_B[n0 * 8 + t + 4] = make_uint4(o0[4], o0[5], o0[6], o0[7]); }
    if (n1 >= 0) { g_B[n1 * 8 + t] = make_uint4(o1[0], o1[1], o1[2], o1[3]); g_B[n1 * 8 + t + 4] = make_uint4(o1[4], o1[5], o1[6], o1[7]); }
  }
  {
    u32 done, it = 0;
    do {
      asm volatile("{.reg .pred q; mbarrier.try_wait.parity.shared.b64 q,[%1],0; selp.u32 %0,1,0,q;}" : "=r"(done) : "r"(sb + S_MB) : "memory");
      if (++it > (1u << 24)) __trap();
    } while (!done);
  }
#pragma unroll
  for (int k = 0; k < 2; k++) {
    int l = ((NT - 1 - tid) >> 2) + k * 128, n = min(cta * NPC + l, NN - 1);
    if (l < NPC) {
      u32 x = sm32[(n * 3) >> 1], y = sm32[((n * 3) >> 1) + 1];
      if (n & 1) { x = __funnelshift_r(x, y, 16); y >>= 16; }
      u32 grp = (l * 171) >> 10, sl = l - grp * 6;
      sl += sl >= 3;
      y = (y & 0xffff) | (grp << 18) | (sl << 28) | (3u << 24);
      u32 a = sb + S_LP + l * 128 + t * 16 + (l & 1) * 64;
      sts128(a, make_uint4(x, y, x, y)); sts128(a ^ 64, make_uint4(x, y, x, y));
    }
  }
  if (warp < 12) {
    float acc[8][4];
#pragma unroll
    for (int j = 0; j < 8; j++) acc[j][0] = acc[j][1] = acc[j][2] = acc[j][3] = 0.f;
    gemm_perm(acc, h0, h1, sb + S_W1, lane);
#pragma unroll
    for (int j = 0; j < 8; j++) {
      u32 a = sb + S_A + (warp * 16 + g) * 128 + ((j ^ g) << 4) + t * 4;
      sts32(a, pack2(acc[j][0], acc[j][1])); sts32(a + 1024, pack2(acc[j][2], acc[j][3]));
    }
  } else if (warp == 12) {
    sm32[S_GC / 4 + lane] = lane;
    if (lane == 0) asm volatile("mbarrier.init.shared.b64 [%0],16;" ::"r"(sb + S_VAR + 8) : "memory");
    sm32[(S_A + 192 * 128) / 4 + lane] = hmul2(sm32[(S_W4 + 2048) / 4 + lane], 0x3f003f00u);
  } else if (tid == 13 * 32) {
    u32 v, it = 0;
    while (((v = ld_acq(&g_cnt[cta * 8])) >> 24) != NCTA) { if (++it > (1u << 26)) __trap(); }
    g_cnt[cta * 8] = 0;
    sm32[S_VAR / 4] = min(v & 0xffffffu, (u32)CAP);
  }
#pragma unroll
  for (int j = 0; j < 4; j++) ldsm4t(sb + S_W4 + ((lane >> 4) * 8 + (lane & 7)) * 128 + (((2 * j + ((lane >> 3) & 1)) ^ (lane & 7)) << 4), W4 + 4 * j);
  ldsm4t(sb + S_W4 + 2176 + (lane >> 3) * 32 + (lane & 1) * 16, wx);
  target = (target / NCTA + 1) * NCTA;
  if (tid == 15 * 32) bar_wait(target);
  if (warp == 15) TM(6);
  __syncthreads();
  TM(7);
  const int cnt = sm32[S_VAR / 4];
  uint2 r[RPT]; u32 gx[RPT], gy[RPT], rv[RPT];
#pragma unroll
  for (int k = 0; k < RPT; k++) r[k] = tid + k * NT < cnt ? __ldcg(&g_list[cta * CAP + tid + k * NT]) : make_uint2(0, ~0u);
  const u32 novf = __ldcg(&g_novf);
  auto st_wh = [&]()  {
    int k = tid >> 3, c = tid & 7, sw = ((k >> 3) & 3) * 2 + (k & 1);
    const u32 hf = 0x3f003f00u;
    st_perm(sb + S_WH, k, c, sw, make_uint4(hmul2(w1.x, hf), hmul2(w1.y, hf), hmul2(w1.z, hf), hmul2(w1.w, hf)));
    st_perm(sb + S_WH + 8192, k, c, k & 7, w2);
  };
  if (tid == 14 * 32) asm volatile("red.release.gpu.global.add.u32 [%0],1;" ::"l"(&g_bar2[32]) : "memory");
  const bool last = cnt > (RPT - 1) * NT + warp * 32;
#pragma unroll
  for (int k = 0; k < RPT; k++) {
    if (k < RPT - 1 || last) {
      u32 s = r[k].x & 0xffff;
      u32 x = sm32[(s * 3) >> 1], y = sm32[((s * 3) >> 1) + 1];
      uint2 pd = *(const uint2*)(smem + S_LP + (lane & 15) * 8 + ((r[k].x >> 9) & 0x7f80));
      rv[k] = ~0u;
      if (r[k].y != ~0u) rv[k] = atomicAdd((u32*)(smem + S_GC + prmt(pd.y, 0, 0x4442)), 128u);
      u32 sh = s << 4;
      x = __funnelshift_r(x, y, sh); y = __funnelshift_r(y, 0, sh);
      x = hsub2(pd.x, x); y = hsub2(pd.y, y);
      u32 qx = hmul2(x, x), qy = hmul2(y, y);
      if (k == 3) pf_ea(0, PB);
      if (k == 9) pf_ea(PB, PC);
      gx[k] = x; gy[k] = pack2(blo(y), blo(qx) + bhi(qx) + blo(qy));
      r[k].y = prmt(r[k].y, pd.y, 0x7210);
      r[k].x = s;
    }
  }
  __syncthreads();
  TM(8);
  pf_ea(PC, PD);
  u32 b2 = target;
  if (tid == 14 * 32) asm volatile("ld.relaxed.gpu.global.u32 %0,[%1];" : "=r"(b2) : "l"(&g_bar2[32]) : "memory");
  u32 ua, ub, pv;
  u32 Ac[8], X[8];
  {
    const u32 c = sm32[S_GC / 4 + lane] >> 7, cp = (c + 15) & ~15u;
    u32 d = min((__reduce_max_sync(~0u, cp) - cp) >> 4, 7u), eq = ~0u, lt = 0;
#pragma unroll
    for (int b = 2; b >= 0; b--) {
      u32 m = __ballot_sync(~0u, (d >> b) & 1);
      if ((d >> b) & 1) { lt |= eq & ~m; eq &= m; } else eq &= ~m;
    }
    const int rank = __popc(lt) + __popc(eq & ((1u << lane) - 1)), slot = rank < 16 ? 2 * rank : 63 - 2 * rank;
    sts32(sb + S_GC + 128 + slot * 4, cp);
    __syncwarp();
    u32 x = lds32(sb + S_GC + 128 + lane * 4);
#pragma unroll
    for (int o = 1; o < 32; o <<= 1) { u32 y = __shfl_up_sync(~0u, x, o); if (lane >= o) x += y; }
    x = __shfl_sync(~0u, x, slot);
    const u32 st = x - cp, st4 = st * 4;
#pragma unroll
    for (int k = 0; k < RPT; k++) {
      if (k < RPT - 1 || last) {
        u32 q = __shfl_sync(~0u, st4, rv[k]) + (rv[k] >> 5);
        if (rv[k] != ~0u) { sts32(sb + S_SO + q, r[k].x); sts32(sb + S_ED + q, r[k].y); sts64(sb + S_G + q * 2, gx[k], gy[k]); }
      }
    }
    int gsel = 2 * warp + (lane >> 4);
    u32 q = __shfl_sync(~0u, st + c, gsel) + (lane & 15), qe = __shfl_sync(~0u, x, gsel);
    if (q < qe) { sts32(sb + S_SO + q * 4, cta * 160 + gsel * 5); sts32(sb + S_ED + q * 4, 0x33000000u | (e0 + gsel * 4)); sts64(sb + S_G + q * 8, 0, 0); }
    u32 pk = (st >> 4) | ((x >> 4) << 10) | (lane * (6 << 20));
    ua = __reduce_max_sync(~0u, slot == 2 * warp ? pk : 0); ub = __reduce_max_sync(~0u, slot == 2 * warp + 1 ? pk : 0);
    int la = ua >> 20, lb = ub >> 20;
    int c8 = lane & 7, ra = (c8 & 3) == 3 ? 192 : la + c8 - (c8 >> 2), rb = (c8 & 3) == 3 ? 192 : lb + c8 - (c8 >> 2);
    u32 aa = sb + S_A + ra * 128 + (((lane >> 3) ^ (ra & 7)) << 4), ab = sb + S_A + rb * 128 + (((lane >> 3) ^ (rb & 7)) << 4);
    ldsm4t(aa, Ac); ldsm4t(aa ^ 64, Ac + 4); ldsm4t(ab, X); ldsm4t(ab ^ 64, X + 4);
    pv = lds32(sb + S_LP + min((t & 2 ? lb : la) + g - (g >> 2), NPC - 1) * 128 + lane * 4);
  }
  const u32 stg = sb + S_STG + warp * 2 * STG;
  const int q4 = lane >> 3, c8 = lane & 7;
  const u64 bptr = (u64)g_B | (c8 * 16), eptr = ((u64)p.ea - 0x60000000u) | ((lane & 1) * 16);
  u32 cpB0 = stg + q4 * 512 + ((c8 ^ (2 * q4)) << 4), cpB1 = cpB0 ^ 16;
  u32 cpE = stg + 2048 + q4 * 128 + ((4 * (((lane >> 1) ^ q4) & 1) + 2 * ((lane >> 2) & 1) + ((lane ^ (q4 >> 1)) & 1)) << 4);
  u32 ldB[4];
#pragma unroll
  for (int mt = 0; mt < 4; mt++) ldB[mt] = stg + (4 * (c8 >> 1) + 2 * (q4 & 1) + (c8 & 1)) * 128 + (((2 * mt + (q4 >> 1)) ^ c8) << 4);
  u32 ldE = stg + 2048 + (c8 >> 1) * 128 + ((4 * (((lane >> 4) ^ (c8 >> 1)) & 1) + 2 * (c8 & 1) + ((q4 ^ (c8 >> 2)) & 1)) << 4);
  u32 tlo = g < 3 ? 0x3fu << (8 * g) : 0, thi = (g >= 4 && g < 7) ? 0x3fu << (8 * (g - 4)) : 0;
  auto opq = [&](u32& v) { v = __shfl_sync(~0u, v, lane); };
  opq(cpB0); opq(cpB1); opq(cpE); opq(ldE); opq(tlo); opq(thi); opq(ldB[0]); opq(ldB[1]); opq(ldB[2]); opq(ldB[3]);
  const u32 to0 = (ua & 1023) * 64;
  u32 aSO = sb + S_SO + q4 * 16 + to0, aE1 = sb + S_ED + (lane >> 1) * 4 + to0, aE4 = sb + S_ED + t * 16 + to0, aG = sb + S_G + c8 * 16 + 2 * to0;
  auto issue = [&](uint4 so, u32 ed, u32 off, int pr) {
    asm volatile("{.reg .b64 a,b,c,d,e; .reg .pred q; setp.ne.s32 q,%10,0;\n"
      "mad.wide.u32 a,%3,128,%8; mad.wide.u32 b,%4,128,%8; mad.wide.u32 c,%5,128,%8; mad.wide.u32 d,%6,128,%8; cvt.u64.u32 e,%7; add.u64 e,e,%9;\n"
      "@q cp.async.cg.shared.global [%0],[a],16; @q cp.async.cg.shared.global [%1+128],[b],16;\n"
      "@q cp.async.cg.shared.global [%0+256],[c],16; @q cp.async.cg.shared.global [%1+384],[d],16;\n"
      "@q cp.async.cg.shared.global [%2],[e],16; cp.async.commit_group;}"
      ::"r"(cpB0 + off), "r"(cpB1 + off), "r"(cpE + off), "r"(so.x), "r"(so.y), "r"(so.z), "r"(so.w), "r"(ed << 5), "l"(bptr), "l"(eptr),
        "r"(pr) : "memory");
  };
  int n = (ub & 1023) - (ua & 1023), c3 = 3 + (ub & 1023) - ((ub >> 10) & 1023);
  if ((int)(b2 - target) < 0) bar_wait(target, &g_bar2[32]);
  if (novf) overflow_path(p, novf);
  __syncthreads();
  TM(9);
#pragma unroll
  for (int k = 0; k < 2; k++) issue(lds128(aSO + k * 64), lds32(aE1 + k * 64), k * STG, n + 3 - c3 > k);
    sts128(sb + S_X + warp * 1024 + lane * 16, make_uint4(X[0], X[1], X[2], X[3]));
    sts128(sb + S_X + warp * 1024 + 512 + lane * 16, make_uint4(X[4], X[5], X[6], X[7]));
  sts32(sb + S_ST + tid * 4, pv);
  if (lane == 0) sts128(sb + S_ST + 2048 + warp * 16, make_uint4(ua >> 20, novf, ub >> 20, 0));
  __syncwarp();
  {
    st_wh();
    __syncwarp();
    if (lane == 0) asm volatile("mbarrier.arrive.shared.b64 _,[%0];" ::"r"(sb + S_VAR + 8) : "memory");
  }
  u32 Sx[3], Sy[3] = {0, 0, 0}, ta, tb;
  auto build = [&](uint4 ed, u32& na, u32& nb, u32 vN) {
    na = prmt(tlo, thi, prmt(ed.x, ed.z, 0x73)); nb = prmt(tlo, thi, prmt(ed.y, ed.w, 0x73));
    na = g == 3 ? vN : na; nb = g == 7 ? vN : nb;
    ta = movm(na); tb = movm(nb);
  };
  Sx[2] = ldsm1t(aG);
  build(lds128(aE4), Sx[0], Sx[1], Sx[2]);
  float seg[4][4], pa[4];
  int gi = 0;
  auto reset = [&]() {
#pragma unroll
    for (int j = 0; j < 4; j++) { seg[j][0] = seg[j][1] = seg[j][2] = seg[j][3] = 0.f; pa[j] = 0.f; }
  };
  float x[4][4], y[4][4];
  u32 ca, cb;
  auto back = [&](int mt, u32 s0, u32 s1) {
    u32 m2 = pack2(silu_h(y[mt][0]), silu_h(y[mt][1])), m3 = pack2(silu_h(y[mt][2]), silu_h(y[mt][3]));
    u32 m0 = pack2(silu_h(x[mt][0]), silu_h(x[mt][1])), m1 = pack2(silu_h(x[mt][2]), silu_h(x[mt][3]));
    mma16(seg[mt], m0, m1, m2, m3, s0, s1);
    ca = hfma2l(m0, wx[mt], mt ? ca : 0x80008000u); cb = hfma2l(m2, wx[mt], mt ? cb : 0x80008000u);
    ca = hfma2h(m1, wx[mt], ca); cb = hfma2h(m3, wx[mt], cb);
  };
  auto body = [&](const u32 off, const u32 to, const u32* C, u32* O) {
    asm volatile("cp.async.wait_group 1;" ::: "memory");
    __syncwarp();
    u32 ef[4], b[4][4];
    auto front = [&](int mt) {
#pragma unroll
      for (int i = 0; i < 4; i++) { x[mt][i] = __uint_as_float(b[mt][i] * 65536u + 0x8000u); y[mt][i] = __uint_as_float(b[mt][i]); }
      mma16(y[mt], W4[4 * mt], W4[4 * mt + 1], W4[4 * mt + 2], W4[4 * mt + 3], ef[2], ef[3]);
      mma16(x[mt], W4[4 * mt], W4[4 * mt + 1], W4[4 * mt + 2], W4[4 * mt + 3], ef[0], ef[1]);
      mma8(y[mt], Ac[2 * mt], Ac[2 * mt + 1], tb);
      mma8(x[mt], Ac[2 * mt], Ac[2 * mt + 1], ta);
    };
    ldsm4(ldE + off, ef);
    ldsm4t(ldB[0] + off, b[0]);
    ldsm4t(ldB[1] + off, b[1]);
    uint4 so = lds128(aSO + to + 128);
    u32 e1 = lds32(aE1 + to + 128);
    back(3, O[0], O[1]);
    u32 keep = g < 4 ? ca : cb, send = g < 4 ? cb : ca;
    front(0);
    { ldsm4t(ldB[2] + off, b[2]); ldsm4t(ldB[3] + off, b[3]); }
    front(1);
    issue(so, e1, off, to ? n > c3 : n >= c3);
    keep = hadd2(keep, __shfl_xor_sync(~0u, send, 16));
    back(0, C[0], C[1]);
    keep = hadd2(keep, __shfl_xor_sync(~0u, keep, 8));
    front(2);
    keep = hadd2(keep, __shfl_xor_sync(~0u, keep, 4));
    back(1, C[0], C[1]);
    mma8(pa, O[0], O[1], hmul2(keep, O[2]));
    front(3);
    uint4 ed = lds128(aE4 + to + 64);
    O[2] = ldsm1t(aG + 2 * to + 128);
    build(ed, O[0], O[1], O[2]);
    back(2, C[0], C[1]);
  };
  auto fin = [&]() {
    uint4 gv = lds128(sb + S_ST + 2048 + warp * 16);
    gi = gv.w;
    n0 = node_of(gv.x, g, cta); n1 = node_of(gv.z, g, cta);
    load_h(p, gi ? n0 : -1, gi ? n1 : -1, t, h0, h1);
    back(3, n ? Sx[0] : Sy[0], n ? Sx[1] : Sy[1]);
    u32 keep = g < 4 ? ca : cb, send = g < 4 ? cb : ca;
    keep = hadd2(keep, __shfl_xor_sync(~0u, send, 16));
    keep = hadd2(keep, __shfl_xor_sync(~0u, keep, 8));
    keep = hadd2(keep, __shfl_xor_sync(~0u, keep, 4));
    mma8(pa, n ? Sx[0] : Sy[0], n ? Sx[1] : Sy[1], hmul2(keep, n ? Sx[2] : Sy[2]));
#pragma unroll
    for (int j = 0; j < 3; j++) { if (n) Sx[j] = 0; else Sy[j] = 0; }
    __syncwarp();
    sts32(sb + S_ST + 2048 + warp * 16 + 12, 1);
    const u32 pv = lds32(sb + S_ST + (tid ^ (2 * gi)) * 4);
    const int nd = gi ? n1 : n0;
    if (gv.y) {
      int na = __shfl_sync(~0u, nd, 8 * t), nb = __shfl_sync(~0u, nd, 8 * t + 4);
#pragma unroll
      for (int mt = 0; mt < 4; mt++) {
        if (na >= 0) { seg[mt][0] += 0.5f * __ldcg(&g_acc[na * 68 + 16 * mt + g]); seg[mt][2] += 0.5f * __ldcg(&g_acc[na * 68 + 16 * mt + 8 + g]); }
        if (nb >= 0) { seg[mt][1] += 0.5f * __ldcg(&g_acc[nb * 68 + 16 * mt + g]); seg[mt][3] += 0.5f * __ldcg(&g_acc[nb * 68 + 16 * mt + 8 + g]); }
      }
      if (nd >= 0 && t < 2) { pa[0] += 0.5f * __ldcg(&g_acc[nd * 68 + 64 + 2 * t]); pa[1] += 0.5f * __ldcg(&g_acc[nd * 68 + 65 + 2 * t]); }
    }
    float u0 = pa[0] + __shfl_xor_sync(~0u, pa[2], 2), u1 = pa[1] + __shfl_xor_sync(~0u, pa[3], 2);
    if (nd >= 0 && t < 2) {
      u32 o = hadd2(pv, pack2(2.f * u0, 2.f * u1));
      unsigned short* po = (unsigned short*)p.out + NN * 64 + nd * 3 + 2 * t;
      po[0] = o & 0xffff;
      if (t == 0) po[1] = o >> 16;
    }
    {
      const u32 xa = sb + S_X + warp * 1024 + lane * 16;
      uint4 x0 = lds128(xa), x1 = lds128(xa + 512);
      Ac[0] = x0.x; Ac[1] = x0.y; Ac[2] = x0.z; Ac[3] = x0.w; Ac[4] = x1.x; Ac[5] = x1.y; Ac[6] = x1.z; Ac[7] = x1.w;
      u32 X[8];
#pragma unroll
      for (int mt = 0; mt < 4; mt++) {
        X[2 * mt] = movm(pack2(seg[mt][0], seg[mt][1]));
        X[2 * mt + 1] = movm(pack2(seg[mt][2], seg[mt][3]));
      }
      sts128(xa, make_uint4(X[0], X[1], X[2], X[3])); sts128(xa + 512, make_uint4(X[4], X[5], X[6], X[7]));
    }
  };
  n *= 2;
#pragma unroll 1
  do {
    reset();
    ca = cb = 0;
#pragma unroll
    for (int j = 0; j < 4; j++) x[3][j] = y[3][j] = 0.f;
    n = __reduce_max_sync(~0u, n);
    const bool odd = n & 1;
    n >>= 1;
    if (n > (int)odd) {
      if (odd) { body(STG, 64, Sy, Sx); aSO += 128; aE1 += 128; aE4 += 128; aG += 256; n -= 2; }
      while (n) {
        body(0, 0, Sx, Sy);
        if (n == 1) break;
        body(STG, 64, Sy, Sx);
        aSO += 128; aE1 += 128; aE4 += 128; aG += 256; n -= 2;
      }
    }
    fin();
    n = 3 * n + 6 - 2 * c3; c3 = 3;
  } while (!gi);
  TM(10);
  {
    u32 done, it = 0;
    do {
      asm volatile("{.reg .pred q; mbarrier.try_wait.parity.shared.b64 q,[%1],0; selp.u32 %0,1,0,q;}" : "=r"(done) : "r"(sb + S_VAR + 8) : "memory");
      if (++it > (1u << 24)) __trap();
    } while (!done);
  }
  {
    u32 X[8];
    *(uint4*)X = lds128(sb + S_X + warp * 1024 + lane * 16); *(uint4*)(X + 4) = lds128(sb + S_X + warp * 1024 + 512 + lane * 16);
    float acc[8][4];
#pragma unroll
    for (int j = 0; j < 8; j++) acc[j][0] = acc[j][1] = acc[j][2] = acc[j][3] = 0.f;
#pragma unroll
    for (int s = 0; s < 4; s++) {
      u32 row = sb + S_WH + 8192 + (16 * s + (lane & 15)) * 128;
#pragma unroll
      for (int j = 0; j < 8; j += 2) {
        u32 w[4]; ldsm4t(row + (((j + (lane >> 4)) ^ c8) << 4), w);
        mma16(acc[j], Ac[2 * s], X[2 * s], Ac[2 * s + 1], X[2 * s + 1], w[0], w[1]);
        mma16(acc[j + 1], Ac[2 * s], X[2 * s], Ac[2 * s + 1], X[2 * s + 1], w[2], w[3]);
      }
    }
    gemm_perm(acc, h0, h1, sb + S_WH, lane);
    u32* a = (u32*)h0; u32* c = (u32*)h1;
#pragma unroll
    for (int j = 0; j < 8; j++) {
      a[j] = hadd2(a[j], pack2(silu_h(acc[j][0]), silu_h(acc[j][1])));
      c[j] = hadd2(c[j], pack2(silu_h(acc[j][2]), silu_h(acc[j][3])));
    }
    uint4* o = (uint4*)p.out;
    if (n0 >= 0) { o[n0 * 8 + t] = h0[0]; o[n0 * 8 + t + 4] = h0[1]; }
    if (n1 >= 0) { o[n1 * 8 + t] = h1[0]; o[n1 * 8 + t + 4] = h1[1]; }
  }
  TM(11);
}

__global__ void fb_zero() { for (int i = blockIdx.x * blockDim.x + threadIdx.x; i < NN * 68; i += gridDim.x * blockDim.x) g_acc[i] = 0.f; }
__global__ void fb_edge(const __grid_constant__ P p) { for (int e = blockIdx.x * 8 + (threadIdx.x >> 5); e < NE; e += gridDim.x * 8) slow_edge(p, e, threadIdx.x & 31); }
__global__ void fb_node(const P p) {
  int n = blockIdx.x, f = threadIdx.x;
  float x = 0.f;
  for (int k = 0; k < 64; k++) x += b2f(p.h[n * 64 + k]) * b2f(p.wh[k * 64 + f]) + rbf(g_acc[n * 68 + k]) * b2f(p.wh[(64 + k) * 64 + f]);
  p.out[n * 64 + f] = __float2bfloat16_rn(b2f(p.h[n * 64 + f]) + rbf(silu_h(0.5f * x)));
  if (f < 3) p.out[NN * 64 + n * 3 + f] = __float2bfloat16_rn(b2f(p.pos[n * 3 + f]) + rbf(g_acc[n * 68 + 64 + f]));
}

extern "C" void kernel_launch(void* const* d_in, const int* in_sizes, int n_in, void* d_out, int out_size) {
  static int mode = -1;
  if (mode < 0) {
    int dev = 0, sms = 0, occ = 0;
    cudaGetDevice(&dev);
    cudaDeviceGetAttribute(&sms, cudaDevAttrMultiProcessorCount, dev);
    cudaError_t e = cudaFuncSetAttribute(egnn_kernel, cudaFuncAttributeMaxDynamicSharedMemorySize, S_END);
    if (e == cudaSuccess) e = cudaOccupancyMaxActiveBlocksPerMultiprocessor(&occ, egnn_kernel, NT, S_END);
    mode = (e == cudaSuccess && occ * sms >= NCTA) ? 1 : 0;
    cudaGetLastError();
  }
  P p;
  p.h = (const __nv_bfloat16*)d_in[0]; p.pos = (const __nv_bfloat16*)d_in[1]; p.ea = (const __nv_bfloat16*)d_in[2];
  p.src = (const int*)d_in[3]; p.dst = (const int*)d_in[4];
  p.we = (const __nv_bfloat16*)d_in[5]; p.wx = (const __nv_bfloat16*)d_in[6]; p.wh = (const __nv_bfloat16*)d_in[7];
  p.out = (__nv_bfloat16*)d_out;
  size_t al = (size_t)d_out;
  for (int i = 0; i < 8; i++) al |= (size_t)d_in[i];
  if (mode == 1 && (al & 31) == 0) {
    egnn_kernel<<<NCTA, NT, S_END>>>(p);
  } else {
    fb_zero<<<512, 256>>>(); fb_edge<<<2048, 256>>>(p); fb_node<<<NN, 64>>>(p);
  }
}
```
